```python
import torch

def _softmax(x, axis=-1):
    return torch.softmax(x, dim=axis)
def _gelu(x):
    return torch.nn.functional.gelu(x, approximate="tanh")
def _silu(x):
    return torch.nn.functional.silu(x)
def _sigmoid(x):
    return torch.sigmoid(x)
def _layernorm(x, axis=-1, eps=1e-5):
    m = x.mean(dim=axis, keepdim=True)
    v = x.var(dim=axis, keepdim=True, unbiased=False)
    return (x - m) / torch.sqrt(v + eps)
def _scatter_add(tgt, idx, src, axis=0):
    return tgt.clone().index_add_(axis, idx, src)
def _segment_sum(src, seg, n):
    out = torch.zeros((n,) + src.shape[1:], dtype=src.dtype)
    return out.index_add_(0, seg, src)
def _pad(x, pw):
    flat = tuple(v for pair in reversed(pw) for v in pair)
    return torch.nn.functional.pad(x, flat)

kernel_name = 'standalone__sliding_block_cached__decode'

def setup_inputs():

    _w = (lambda a: (lambda t: t.to(torch.bfloat16) if t.is_floating_point() else t)(torch.as_tensor(a)))
    B, Sq, D = 2, 1, 576
    Hq, Hkv, Sk, Dh = 32, 16, 32768, 128
    assert Hq % Hkv == 0, (Hq, Hkv)
    return {
        "x": _w((lambda *s: torch.randn(*s, dtype=torch.bfloat16) * 0.8)(B, Sq, D)),
        "k_cache": _w((lambda *s: torch.randn(*s, dtype=torch.bfloat16) * 0.8)(B, Hkv, Sk, Dh)),
        "v_cache": _w((lambda *s: torch.randn(*s, dtype=torch.bfloat16) * 0.05)(B, Hkv, Sk, Dh)),
        "wq": _w((lambda *s: torch.randn(*s, dtype=torch.bfloat16) * 0.8)(D, Hq * Dh) * (D ** -0.5)),
        "wo": _w((lambda *s: torch.randn(*s, dtype=torch.bfloat16) * 0.05)(Hq * Dh, D) * ((Hq * Dh) ** -0.5)),
    }

def reference(x, k_cache, v_cache, wq, wo):
    B, Sq, D = x.shape
    Hq, Dh = 32, 128
    Hkv, Sk = k_cache.shape[1], k_cache.shape[2]
    W = min(4096, max(256, Sk // 4))
    rep = Hq // Hkv
    q = (lambda x, *d: x.permute(*d))((x @ wq).reshape(B, Sq, Hq, Dh), 0, 2, 1, 3)
    k = (lambda x, n, axis: torch.repeat_interleave(x, n, dim=axis))(k_cache[:, :, Sk - W:, :], rep, axis=1)
    v = (lambda x, n, axis: torch.repeat_interleave(x, n, dim=axis))(v_cache[:, :, Sk - W:, :], rep, axis=1)
    scores = torch.einsum("bhqd,bhkd->bhqk", q, k) * (Dh ** -0.5)
    p = _softmax(scores, axis=-1)
    o = torch.einsum("bhqk,bhkd->bhqd", p, v)
    return (lambda x, *d: x.permute(*d))(o, 0, 2, 1, 3).reshape(B, Sq, Hq * Dh) @ wo
```

```cpp
#include <cuda_runtime.h>
#include <cuda_bf16.h>
#include <cuda.h>
#include <stdint.h>

#define WINDOW 12
#define PACE_NS 326
#define PACE_T0 500
#define GATE_CYCLES 1200
#define HINT_SLACK 16
#define PREWRITE_CHUNK 44

namespace {

constexpr int D_MODEL = 576;
constexpr int NQ      = 4096;
constexpr int SK      = 32768;
constexpr int WIN     = 4096;
constexpr int NCTA    = 64;
constexpr int NTHREADS = 320;
constexpr int NREAL = 288;
constexpr int NSLOT   = 13;
constexpr int CHUNK   = 16384;
constexpr int NSTAGE  = 16;
constexpr int NCHUNK  = NSTAGE * 4;
constexpr int WO_PIECES = 4;
constexpr int WO_PITCH = 304;
constexpr int WO_PIECE = 64 * WO_PITCH;
constexpr int OS_PITCH = 544;
constexpr int CNT_PER_LAUNCH = NCTA;

constexpr int WQ_SLOT0 = 8;
constexpr int SM_RING = 0;
constexpr int SM_WQ   = WQ_SLOT0 * CHUNK;
constexpr int SM_QRED = SM_WQ + 576 * 128;
constexpr int SM_WO   = 0;
constexpr int SM_RED  = NSLOT * CHUNK;
constexpr int SM_XO   = SM_RED + 8192;
constexpr int SM_XML  = SM_XO + 4 * OS_PITCH;
constexpr int SM_QS   = SM_XML + 64;
constexpr int SM_M    = SM_QS + 512;
constexpr int SM_L    = SM_M + 96;
constexpr int SM_DUMMY = SM_L + 96;
constexpr int SM_BAR  = SM_DUMMY + 1024;
constexpr int SM_TOTAL = SM_BAR + 16 * NSLOT + 48;
static_assert(SM_QRED + 4096 <= NSLOT * CHUNK && WO_PIECES * WO_PIECE <= 5 * CHUNK, "smem map");

constexpr float SCALE_LOG2 = 0.08838834764831845f * 1.4426950408889634f;
constexpr int SPIN_LIMIT = 1 << 20;

__device__ unsigned int g_cnt;
__device__ unsigned long long g_y[16 * 2 * D_MODEL];
#define TS(i)
#define TS_DECL
#define TS_DUMP

__device__ __forceinline__ long long gtime() { long long t; asm volatile("mov.u64 %0, %globaltimer;" : "=l"(t)); return t; }
__device__ __forceinline__ uint32_t smem_u32(const void* p) { return (uint32_t)__cvta_generic_to_shared(p); }
__device__ __forceinline__ void mbar_init(uint32_t bar, uint32_t cnt) {
    asm volatile("mbarrier.init.shared::cta.b64 [%0], %1;" :: "r"(bar), "r"(cnt) : "memory");
}
__device__ __forceinline__ void mbar_expect_tx(uint32_t bar, uint32_t bytes) {
    asm volatile("mbarrier.arrive.expect_tx.shared::cta.b64 _, [%0], %1;" :: "r"(bar), "r"(bytes) : "memory");
}
__device__ __forceinline__ void mbar_arrive(uint32_t bar) {
    asm volatile("mbarrier.arrive.shared::cta.b64 _, [%0];" :: "r"(bar) : "memory");
}
__device__ __forceinline__ void mbar_wait(uint32_t bar, uint32_t parity) {
    uint32_t ok;
    int it = 0;
    do {
        asm volatile("{\n.reg .pred p;\nmbarrier.try_wait.parity.shared::cta.b64 p, [%1], %2;\nselp.u32 %0, 1, 0, p;\n}"
                     : "=r"(ok) : "r"(bar), "r"(parity) : "memory");
    } while (!ok && ++it < SPIN_LIMIT);
}
__device__ __forceinline__ void mbar_wait_cluster(uint32_t bar, uint32_t parity) {
    uint32_t ok;
    int it = 0;
    do {
        asm volatile("{\n.reg .pred p;\nmbarrier.try_wait.parity.shared::cta.b64 p, [%1], %2;\nselp.u32 %0, 1, 0, p;\n}"
                     : "=r"(ok) : "r"(bar), "r"(parity) : "memory");
    } while (!ok && ++it < SPIN_LIMIT);
}
__device__ __forceinline__ uint32_t mapa(uint32_t addr, uint32_t rank) {
    uint32_t r; asm("mapa.shared::cluster.u32 %0, %1, %2;" : "=r"(r) : "r"(addr), "r"(rank)); return r;
}
__device__ __forceinline__ void st_async_b32(uint32_t raddr, uint32_t v, uint32_t rbar, bool pr) {
    asm volatile("{\n.reg .pred q;\nsetp.ne.u32 q, %3, 0;\n@q st.async.weak.shared::cluster.mbarrier::complete_tx::bytes.b32 [%0], %1, [%2];\n}"
                 :: "r"(raddr), "r"(v), "r"(rbar), "r"((uint32_t)pr) : "memory");
}
__device__ __forceinline__ void cp_async16(uint32_t dst, const void* src) {
    asm volatile("cp.async.cg.shared.global [%0], [%1], 16;" :: "r"(dst), "l"(src) : "memory");
}
__device__ __forceinline__ uint2 lds64(uint32_t addr) {
    uint2 v; asm volatile("ld.shared.v2.u32 {%0,%1}, [%2];" : "=r"(v.x), "=r"(v.y) : "r"(addr)); return v;
}
__device__ __forceinline__ uint32_t lds32(uint32_t addr) {
    uint32_t v; asm volatile("ld.shared.u32 %0, [%1];" : "=r"(v) : "r"(addr)); return v;
}
__device__ __forceinline__ void ldsm4t(uint32_t addr, uint32_t& a0, uint32_t& a1, uint32_t& a2, uint32_t& a3) {
    asm volatile("ldmatrix.sync.aligned.m8n8.x4.trans.shared.b16 {%0,%1,%2,%3}, [%4];"
                 : "=r"(a0), "=r"(a1), "=r"(a2), "=r"(a3) : "r"(addr));
}
__device__ __forceinline__ void bulk_g2s(uint32_t dst, const void* src, uint32_t bytes, uint32_t bar, uint64_t pol) {
    asm volatile("cp.async.bulk.shared::cluster.global.mbarrier::complete_tx::bytes.L2::cache_hint [%0], [%1], %2, [%3], %4;"
                 :: "r"(dst), "l"(src), "r"(bytes), "r"(bar), "l"(pol) : "memory");
}
__device__ __forceinline__ void tma2d_g2s(uint32_t dst, const CUtensorMap* map, int c0, int c1, uint32_t bar, uint64_t pol) {
    asm volatile("cp.async.bulk.tensor.2d.shared::cluster.global.mbarrier::complete_tx::bytes.L2::cache_hint [%0], [%1, {%2, %3}], [%4], %5;"
                 :: "r"(dst), "l"(map), "r"(c0), "r"(c1), "r"(bar), "l"(pol) : "memory");
}
__device__ __forceinline__ uint4 ldg_stream(const void* p) {
    uint4 v;
    asm volatile("ld.global.nc.L1::no_allocate.v4.u32 {%0,%1,%2,%3}, [%4];" : "=r"(v.x), "=r"(v.y), "=r"(v.z), "=r"(v.w) : "l"(p));
    return v;
}
__device__ __forceinline__ uint4 lds128(uint32_t addr) {
    uint4 v;
    asm volatile("ld.shared.v4.u32 {%0,%1,%2,%3}, [%4];" : "=r"(v.x), "=r"(v.y), "=r"(v.z), "=r"(v.w) : "r"(addr));
    return v;
}
__device__ __forceinline__ void ll_store(unsigned long long* p, uint32_t payload, uint32_t epoch, bool pr) {
    asm volatile("{\n.reg .pred q;\n.reg .b64 v;\nsetp.ne.u32 q, %3, 0;\nmov.b64 v, {%1, %2};\n@q st.relaxed.gpu.global.b64 [%0], v;\n}"
                 :: "l"(p), "r"(payload), "r"(epoch), "r"((uint32_t)pr) : "memory");
}
__device__ __forceinline__ void ll_load4(const unsigned long long* p, uint32_t (&f)[4], uint32_t (&e)[4], bool pr) {
    asm volatile("{\n.reg .pred q;\n.reg .b64 a, b, c, d;\nsetp.ne.u32 q, %9, 0;\n"
                 "mov.b64 a, 0;\nmov.b64 b, 0;\nmov.b64 c, 0;\nmov.b64 d, 0;\n"
                 "@q ld.relaxed.gpu.global.v2.b64 {a, b}, [%8];\n@q ld.relaxed.gpu.global.v2.b64 {c, d}, [%8+16];\n"
                 "mov.b64 {%0, %4}, a;\nmov.b64 {%1, %5}, b;\nmov.b64 {%2, %6}, c;\nmov.b64 {%3, %7}, d;\n}"
                 : "=r"(f[0]), "=r"(f[1]), "=r"(f[2]), "=r"(f[3]), "=r"(e[0]), "=r"(e[1]), "=r"(e[2]), "=r"(e[3])
                 : "l"(p), "r"((uint32_t)pr) : "memory");
}
__device__ __forceinline__ void mma16816(float (&c)[4], uint32_t a0, uint32_t a1, uint32_t a2, uint32_t a3, uint32_t b0, uint32_t b1) {
    asm volatile("mma.sync.aligned.m16n8k16.row.col.f32.bf16.bf16.f32 {%0,%1,%2,%3}, {%4,%5,%6,%7}, {%8,%9}, {%0,%1,%2,%3};"
                 : "+f"(c[0]), "+f"(c[1]), "+f"(c[2]), "+f"(c[3])
                 : "r"(a0), "r"(a1), "r"(a2), "r"(a3), "r"(b0), "r"(b1));
}
__device__ __forceinline__ void mma1688(float (&c)[4], uint32_t a0, uint32_t a1, uint32_t b0) {
    asm volatile("mma.sync.aligned.m16n8k8.row.col.f32.bf16.bf16.f32 {%0,%1,%2,%3}, {%4,%5}, {%6}, {%0,%1,%2,%3};"
                 : "+f"(c[0]), "+f"(c[1]), "+f"(c[2]), "+f"(c[3]) : "r"(a0), "r"(a1), "r"(b0));
}
__device__ __forceinline__ float ex2(float x) { float y; asm("ex2.approx.ftz.f32 %0, %1;" : "=f"(y) : "f"(x)); return y; }
__device__ __forceinline__ uint32_t pack_bf16(float lo, float hi) {
    uint32_t r; asm("cvt.rn.bf16x2.f32 %0, %1, %2;" : "=r"(r) : "f"(hi), "f"(lo)); return r;
}
__device__ __forceinline__ float bf_lo(uint32_t v) { return __uint_as_float(v << 16); }
__device__ __forceinline__ float bf_hi(uint32_t v) { return __uint_as_float(v & 0xffff0000u); }
__device__ __forceinline__ int f2ord(float f) { int i = __float_as_int(f); return i ^ ((i >> 31) & 0x7fffffff); }
__device__ __forceinline__ float ord2f(int i) { return __int_as_float(i ^ ((i >> 31) & 0x7fffffff)); }
__device__ __forceinline__ void bar_sync(int id, int n) { asm volatile("bar.sync %0, %1;" :: "r"(id), "r"(n) : "memory"); }
__device__ __forceinline__ void bar_arrive(int id, int n) { asm volatile("bar.arrive %0, %1;" :: "r"(id), "r"(n) : "memory"); }
__device__ __forceinline__ bool elect_one() {
    uint32_t p;
    asm volatile("{\n.reg .pred q;\nelect.sync _|q, 0xffffffff;\nselp.u32 %0, 1, 0, q;\n}" : "=r"(p));
    return p != 0;
}
__device__ __forceinline__ void cluster_arrive_release() { asm volatile("barrier.cluster.arrive.release.aligned;" ::: "memory"); }
__device__ __forceinline__ void cluster_arrive_relaxed() { asm volatile("barrier.cluster.arrive.relaxed.aligned;" ::: "memory"); }
__device__ __forceinline__ void cluster_wait() { asm volatile("barrier.cluster.wait.acquire.aligned;" ::: "memory"); }

__global__ void __cluster_dims__(4, 1, 1) __launch_bounds__(NTHREADS, 1)
fused_decode_kernel(const __nv_bfloat16* __restrict__ x, const __nv_bfloat16* __restrict__ kc,
                    const __nv_bfloat16* __restrict__ vc, const __nv_bfloat16* __restrict__ wq,
                    __nv_bfloat16* __restrict__ out, const __grid_constant__ CUtensorMap wo_map)
{
    extern __shared__ __align__(1024) unsigned char smem[];
    const uint32_t sb = smem_u32(smem);
    const int tid = threadIdx.x, lane = tid & 31;
    const int warp = __shfl_sync(0xffffffffu, tid >> 5, 0);
    const int cta = blockIdx.x;
    const int hkv = cta >> 2, rank = cta & 3, bb = rank >> 1, split = rank & 1;
    const int g = lane >> 2, t = lane & 3;
    const uint32_t bar_full = sb + SM_BAR, bar_empty = bar_full + 8 * NSLOT;
    const uint32_t bar_wo = bar_empty + 8 * NSLOT, bar_xq = bar_wo + 32, bar_xo = bar_wo + 40;
    const bool real = warp != 9;
    uint32_t epoch = 0;
    TS_DECL
    TS(0);

    if (warp == 8) {
        const long long t_start = gtime();
        if (elect_one()) {
            #pragma unroll
            for (int i = 0; i < NSLOT; i++) { mbar_init(bar_full + 8 * i, 1); mbar_init(bar_empty + 8 * i, 4); }
            #pragma unroll
            for (int i = 0; i < WO_PIECES; i++) mbar_init(bar_wo + 8 * i, 1);
            mbar_init(bar_xq, 1); mbar_init(bar_xo, 1);
            mbar_expect_tx(bar_xq, 512);
            mbar_expect_tx(bar_xo, 4 * (512 + 16));
            asm volatile("fence.mbarrier_init.release.cluster;" ::: "memory");
            asm volatile("prefetch.tensormap [%0];" :: "l"(&wo_map) : "memory");
        }
        __syncwarp();
        cluster_arrive_relaxed();
        bar_arrive(1, NREAL);
        {
            uint64_t pol; asm volatile("createpolicy.fractional.L2::evict_first.b64 %0, 1.0;" : "=l"(pol));
            const size_t row0 = (size_t)(bb * 16 + hkv) * SK + (SK - WIN) + split * 128;
            const unsigned char* kp = reinterpret_cast<const unsigned char*>(kc) + row0 * 256;
            const unsigned char* vp = reinterpret_cast<const unsigned char*>(vc) + row0 * 256;
            long long t_next = t_start + PACE_T0;
            uint32_t slot = 0, pass = 0;
            uint32_t lslot = 0, lph = 0;
            #pragma unroll 1
            for (int i = 0; i < NCHUNK; i++) {
                if (i >= WINDOW) {
                    mbar_wait(bar_full + 8 * lslot, lph);
                    if (++lslot == NSLOT) { lslot = 0; lph ^= 1; }
                }
                mbar_wait(bar_empty + 8 * slot, (pass ^ (slot < WQ_SLOT0 ? 1 : 0)) & 1);
                while (gtime() < t_next) ;
                t_next += PACE_NS;
                if (elect_one()) {
                    mbar_expect_tx(bar_full + 8 * slot, CHUNK);
                    bulk_g2s(sb + SM_RING + slot * CHUNK, ((i & 2) ? vp : kp) + (i & 1) * CHUNK, CHUNK, bar_full + 8 * slot, pol);
                }
                if ((i & 3) == 3) { kp += 4 * CHUNK; vp += 4 * CHUNK; }
                if (++slot == NSLOT) { slot = 0; pass ^= 1; }
                if (i == PREWRITE_CHUNK) {
                    unsigned long long* yp = &g_y[hkv * (2 * D_MODEL) + rank * 144];
                    #pragma unroll 1
                    for (int j = lane; j < 144; j += 32) { ll_store(yp + j, 0, 0, true); ll_store(yp + D_MODEL + j, 0, 0, true); }
                    epoch = __ldcg(&g_cnt) / CNT_PER_LAUNCH + 1;
                }
            }
            mbar_wait(bar_empty + 0, 0);
            #pragma unroll 1
            for (int p = 0; p < WO_PIECES; p++) {
                mbar_wait(bar_full + 8 * lslot, lph);
                if (++lslot == NSLOT) { lslot = 0; lph ^= 1; }
                mbar_wait(bar_empty + 8 * (p + 1), 0);
                while (gtime() < t_next) ;
                t_next += PACE_NS * WO_PIECE / CHUNK;
                if (elect_one()) {
                    mbar_expect_tx(bar_wo + 8 * p, WO_PIECE);
                    tma2d_g2s(sb + SM_WO + p * WO_PIECE, &wo_map, rank * 144, hkv * 256 + p * 64, bar_wo + 8 * p, pol);
                }
            }
        }
        cluster_wait();
        bar_sync(2, NREAL);
        if (lane < 4) {
            const int h = lane >> 1;
            const float* sm = reinterpret_cast<const float*>(smem + SM_M) + h;
            const float* sl = reinterpret_cast<const float*>(smem + SM_L) + h;
            float M = sm[0];
            #pragma unroll
            for (int w = 1; w < 8; w++) M = fmaxf(M, sm[2 * w]);
            float L = 0.f;
            #pragma unroll
            for (int w = 0; w < 8; w++) L = fmaf(ex2(sm[2 * w] - M), sl[2 * w], L);
            const float v = (lane & 1) ? L : M;
            #pragma unroll
            for (int r = 0; r < 4; r++)
                st_async_b32(mapa(sb + SM_XML + (rank * 4 + lane) * 4, r), __float_as_uint(v), mapa(bar_xo, r), true);
        }
        __syncwarp();
    } else {
        if (real) {
            const uint32_t wq_w = sb + SM_WQ + warp * (72 * 128);
            {
                const int rr = lane >> 3, ch = lane & 7;
                const uint32_t d0 = wq_w + rr * 128 + ((ch ^ rr) << 4), d1 = wq_w + (4 + rr) * 128 + ((ch ^ (4 + rr)) << 4);
                const unsigned char* src = reinterpret_cast<const unsigned char*>(wq) + (size_t)(warp * 72 + rr) * (NQ * 2) + cta * 128 + ch * 16;
                #pragma unroll
                for (int i = 0; i < 18; i++) {
                    cp_async16(((i & 1) ? d1 : d0) + (i >> 1) * 1024, src + (size_t)i * 4 * NQ * 2);
                    if ((i & 3) == 3 || i == 17) asm volatile("cp.async.commit_group;" ::: "memory");
                }
            }
            uint32_t xb[9];
            {
                const uint32_t* xw = reinterpret_cast<const uint32_t*>(x + (g & 1) * D_MODEL + warp * 72) + t;
                #pragma unroll
                for (int i = 0; i < 9; i++) xb[i] = __ldg(xw + i * 4);
            }
            epoch = __ldcg(&g_cnt) / CNT_PER_LAUNCH + 1;
            cluster_arrive_relaxed();
            bar_sync(1, NREAL);
            cluster_wait();
            #pragma unroll 1
            for (int pass = 0; pass < 2; pass++) {
                float c[4][4];
                #pragma unroll
                for (int m = 0; m < 4; m++) { c[m][0] = c[m][1] = c[m][2] = c[m][3] = 0.f; }
                const uint32_t wa = wq_w + ((lane & 7) + ((lane >> 4) & 1) * 8) * 128;
                const uint32_t sw = (lane >> 3) & 1, l7 = lane & 7;
                #pragma unroll
                for (int k = 0; k < 4; k++) {
                    if (pass) {
                        if (k == 0) asm volatile("cp.async.wait_group 4;" ::: "memory");
                        if (k == 1) asm volatile("cp.async.wait_group 3;" ::: "memory");
                        if (k == 2) asm volatile("cp.async.wait_group 2;" ::: "memory");
                        if (k == 3) asm volatile("cp.async.wait_group 1;" ::: "memory");
                    }
                    __syncwarp();
                    #pragma unroll
                    for (int m = 0; m < 4; m++) {
                        uint32_t a0, a1, a2, a3;
                        ldsm4t(wa + k * 2048 + (((2 * m + sw) ^ l7) << 4), a0, a1, a2, a3);
                        mma16816(c[m], a0, a1, a2, a3, xb[2 * k], xb[2 * k + 1]);
                    }
                }
                if (pass) asm volatile("cp.async.wait_group 0;" ::: "memory");
                __syncwarp();
                {
                    const uint32_t wt = wq_w + (64 + l7) * 128;
                    #pragma unroll
                    for (int m = 0; m < 4; m += 2) {
                        uint32_t a0, a1, a2, a3;
                        ldsm4t(wt + (((2 * m + (lane >> 3)) ^ l7) << 4), a0, a1, a2, a3);
                        mma1688(c[m], a0, a1, xb[8]);
                        mma1688(c[m + 1], a2, a3, xb[8]);
                    }
                }
                TS(9);
                {
                    float* qr = reinterpret_cast<float*>(smem + SM_QRED) + warp * 128 + t * 16 + g;
                    const float v0 = t == 0 ? c[0][0] : t == 1 ? c[1][0] : t == 2 ? c[2][0] : c[3][0];
                    const float v1 = t == 0 ? c[0][1] : t == 1 ? c[1][1] : t == 2 ? c[2][1] : c[3][1];
                    const float v2 = t == 0 ? c[0][2] : t == 1 ? c[1][2] : t == 2 ? c[2][2] : c[3][2];
                    const float v3 = t == 0 ? c[0][3] : t == 1 ? c[1][3] : t == 2 ? c[2][3] : c[3][3];
                    qr[0] = v0; qr[64] = v1; qr[8] = v2; qr[72] = v3;
                }
                if (pass) bar_sync(5, 256);
                TS(1);
                if (tid < 128) {
                    const float* qr = reinterpret_cast<const float*>(smem + SM_QRED) + tid;
                    float s = 0.f;
                    #pragma unroll
                    for (int w = 0; w < 8; w++) s += qr[w * 128];
                    const float o = __shfl_xor_sync(0xffffffffu, s, 1);
                    const uint32_t pk = (tid & 1) ? pack_bf16(o, s) : pack_bf16(s, o);
                    const uint32_t dst = (tid >> 6) * 2 + (tid & 1);
                    st_async_b32(mapa(sb + SM_QS + (rank * 64 + (tid & 62)) * 2, dst), pk, mapa(bar_xq, dst), pass != 0);
                    if (pass) {
                        asm volatile("fence.proxy.async.shared::cta;" ::: "memory");
                        __syncwarp();
                        if (lane == 0) {
                            #pragma unroll
                            for (int i = WQ_SLOT0; i < NSLOT; i++) mbar_arrive(bar_empty + 8 * i);
                        }
                    }
                }
            }
            mbar_wait(bar_xq, 0);
            TS(2);
        } else {
            cluster_arrive_relaxed();
        }
        uint32_t qb[4][2];
        {
            const int hh = g & 1, par = (g >> 1) & 1, eta = g >> 2;
            #pragma unroll
            for (int j = 0; j < 4; j++) {
                const uint32_t a = sb + SM_QS + hh * 256 + (4 * (j ^ par) + t) * 16 + eta * 4;
                qb[j][0] = lds32(a); qb[j][1] = lds32(a + 8);
            }
        }

        float acc[8][4];
        #pragma unroll
        for (int e = 0; e < 8; e++) { acc[e][0] = acc[e][1] = acc[e][2] = acc[e][3] = 0.f; }
        float m0 = -INFINITY, m1 = -INFINITY, mown = -INFINITY, lsum = 0.f;
        const bool valid = ((t ^ g) & 1) == 0;
        const bool hi = t & 2;
        const uint32_t kc0 = sb + SM_RING + ((warp & 3) * 16 + g) * 256 + (4 * (g & 1) + t) * 16;
        const uint32_t voff = sb + SM_RING + ((warp & 3) * 16 + 2 * t) * 256 + ((g ^ (2 * t)) * 16);
        const int src0 = 4 * (2 * t) + 2 * (g & 1), src1 = 4 * (2 * t + 1) + 1 + 2 * (g & 1);
        const bool bsel = (g >> 1) == t;
        const int last = real ? NSTAGE - 1 : 0;
        uint32_t slot = (warp >> 2) & 1, ph = 0;
        #pragma unroll 1
        for (int it = 0; it <= last; it++) {
            if (real) mbar_wait(bar_full + 8 * slot, ph);
            float ca[4] = {0.f, 0.f, 0.f, 0.f}, cb[4] = {0.f, 0.f, 0.f, 0.f};
            {
                uint4 ka[4], kh[4];
                #pragma unroll
                for (int j = 0; j < 4; j++) {
                    const uint32_t a = slot * CHUNK + ((kc0 ^ ((j & 1) * 64)) + (j >> 1) * 128);
                    ka[j] = lds128(a); kh[j] = lds128(a + 8 * 256);
                }
                #pragma unroll
                for (int j = 0; j < 4; j++) {
                    mma16816(ca, ka[j].x, ka[j].y, ka[j].z, ka[j].w, qb[j][0], qb[j][1]);
                    mma16816(cb, kh[j].x, kh[j].y, kh[j].z, kh[j].w, qb[j][0], qb[j][1]);
                }
            }
            __syncwarp();
            if (real && elect_one()) mbar_arrive(bar_empty + 8 * slot);
            slot += 2; if (slot >= NSLOT) { slot -= NSLOT; ph ^= 1; }
            const float sa = ((hi ? ca[3] : ca[0]) + __shfl_xor_sync(0xffffffffu, hi ? ca[2] : ca[1], 2)) * SCALE_LOG2;
            const float sb2 = ((hi ? cb[3] : cb[0]) + __shfl_xor_sync(0xffffffffu, hi ? cb[2] : cb[1], 2)) * SCALE_LOG2;
            const float mx = fmaxf(sa, sb2);
            if (__any_sync(0xffffffffu, valid && mx > mown) || !real) {
                const int ko = f2ord(mx);
                const float n0 = fmaxf(m0, ord2f(__reduce_max_sync(0xffffffffu, (valid && !hi) ? ko : (int)0x80000000)));
                const float n1 = fmaxf(m1, ord2f(__reduce_max_sync(0xffffffffu, (valid && hi) ? ko : (int)0x80000000)));
                const float a0 = ex2(m0 - n0), a1 = ex2(m1 - n1);
                #pragma unroll
                for (int e = 0; e < 8; e++) { acc[e][0] *= a0; acc[e][1] *= a1; acc[e][2] *= a0; acc[e][3] *= a1; }
                lsum *= hi ? a1 : a0;
                m0 = n0; m1 = n1; mown = hi ? n1 : n0;
            }
            const float pa = ex2(sa - mown), pb = ex2(sb2 - mown);
            lsum += pa + pb;
            const uint32_t y = pack_bf16(pa, pb);
            uint32_t b0 = __shfl_sync(0xffffffffu, y, src0), b1 = __shfl_sync(0xffffffffu, y, src1);
            b0 = bsel ? b0 : 0u; b1 = bsel ? b1 : 0u;
            if (real) mbar_wait(bar_full + 8 * slot, ph);
            const uint32_t vb = slot * CHUNK + voff;
            const uint4 vA0 = lds128(vb), vB0 = lds128(vb + 128);
            const uint4 vA1 = lds128(vb + 8 * 256), vB1 = lds128(vb + 8 * 256 + 128);
            const uint4 vA2 = lds128(vb + 256), vB2 = lds128(vb + 256 + 128);
            const uint4 vA3 = lds128(vb + 9 * 256), vB3 = lds128(vb + 9 * 256 + 128);
            const uint32_t A0[4] = {vA0.x, vA0.y, vA0.z, vA0.w}, A1[4] = {vA1.x, vA1.y, vA1.z, vA1.w};
            const uint32_t A2[4] = {vA2.x, vA2.y, vA2.z, vA2.w}, A3[4] = {vA3.x, vA3.y, vA3.z, vA3.w};
            const uint32_t B0[4] = {vB0.x, vB0.y, vB0.z, vB0.w}, B1[4] = {vB1.x, vB1.y, vB1.z, vB1.w};
            const uint32_t B2[4] = {vB2.x, vB2.y, vB2.z, vB2.w}, B3[4] = {vB3.x, vB3.y, vB3.z, vB3.w};
            #pragma unroll
            for (int r = 0; r < 4; r++) {
                mma16816(acc[2 * r], __byte_perm(A0[r], A1[r], 0x5410), __byte_perm(B0[r], B1[r], 0x5410),
                         __byte_perm(A2[r], A3[r], 0x5410), __byte_perm(B2[r], B3[r], 0x5410), b0, b1);
                mma16816(acc[2 * r + 1], __byte_perm(A0[r], A1[r], 0x7632), __byte_perm(B0[r], B1[r], 0x7632),
                         __byte_perm(A2[r], A3[r], 0x7632), __byte_perm(B2[r], B3[r], 0x7632), b0, b1);
            }
            __syncwarp();
            if (real && elect_one()) mbar_arrive(bar_empty + 8 * slot);
            slot += 2; if (slot >= NSLOT) { slot -= NSLOT; ph ^= 1; }
        }
        TS(3);
        const int ti = tid & 255;
        {
            const bool t1 = t & 2, t0 = t & 1;
            float h16[16];
            #pragma unroll
            for (int e = 0; e < 8; e++) {
                #pragma unroll
                for (int h = 0; h < 2; h++) {
                    const float s = t1 ? acc[e][h] : acc[e][2 + h];
                    const float k = t1 ? acc[e][2 + h] : acc[e][h];
                    h16[h * 8 + e] = k + __shfl_xor_sync(0xffffffffu, s, 18);
                }
            }
            float o8[8];
            #pragma unroll
            for (int e = 0; e < 8; e++) {
                const float s = t0 ? h16[e] : h16[8 + e];
                const float k = t0 ? h16[8 + e] : h16[e];
                o8[e] = k + __shfl_xor_sync(0xffffffffu, s, 9);
            }
            const int c = g ^ (2 * t);
            float* myred = reinterpret_cast<float*>(smem + (real ? SM_RED + warp * 1024 : SM_DUMMY));
            float4* dst = reinterpret_cast<float4*>(&myred[(t & 1) * 128 + (t >> 1) * 64 + c * 8]);
            dst[t1 ? 1 : 0] = t1 ? make_float4(o8[4], o8[5], o8[6], o8[7]) : make_float4(o8[0], o8[1], o8[2], o8[3]);
            dst[t1 ? 0 : 1] = t1 ? make_float4(o8[0], o8[1], o8[2], o8[3]) : make_float4(o8[4], o8[5], o8[6], o8[7]);
            float l = valid ? lsum : 0.f;
            l += __shfl_xor_sync(0xffffffffu, l, 5);
            l += __shfl_xor_sync(0xffffffffu, l, 8);
            l += __shfl_xor_sync(0xffffffffu, l, 16);
            if (lane == 0 || lane == 2) {
                reinterpret_cast<float*>(smem + SM_L)[warp * 2 + (lane >> 1)] = l;
                reinterpret_cast<float*>(smem + SM_M)[warp * 2 + (lane >> 1)] = mown;
            }
            TS(10);
            if (real) bar_sync(2, NREAL);
            TS(11);
            const float* sm = reinterpret_cast<const float*>(smem + SM_M) + (ti >> 7);
            float M = sm[0];
            #pragma unroll
            for (int w = 1; w < 8; w++) M = fmaxf(M, sm[2 * w]);
            float o = 0.f;
            #pragma unroll
            for (int w = 0; w < 8; w++) o = fmaf(ex2(sm[2 * w] - M), reinterpret_cast<const float*>(smem + SM_RED + w * 1024)[ti], o);
            const float on = __shfl_xor_sync(0xffffffffu, o, 1);
            const uint32_t pk = (ti & 1) ? pack_bf16(on, o) : pack_bf16(o, on);
            const int ke = ti & ~1;
            const uint32_t pos = (ke & ~15) + ((ke & 7) >> 1) * 4 + ((ke >> 3) & 1) * 2;
            const uint32_t la = sb + SM_XO + rank * OS_PITCH + pos * 2, r0 = (ti & 1) * 2;
            st_async_b32(mapa(la, r0), pk, mapa(bar_xo, r0), real);
            st_async_b32(mapa(la, r0 + 1), pk, mapa(bar_xo, r0 + 1), real);
        }
        TS(4);
    }

    {
        const int w9 = real ? warp : 0;
        uint32_t wf[16][4];
        const uint32_t wa = sb + SM_WO + ((lane & 7) + ((lane >> 4) & 1) * 8) * WO_PITCH + (w9 * 16 + ((lane >> 3) & 1) * 8) * 2;
        #pragma unroll
        for (int p = 0; p < WO_PIECES - 1; p++) {
            if (real) mbar_wait(bar_wo + 8 * p, 0);
            #pragma unroll
            for (int k = 0; k < 4; k++) ldsm4t(wa + (p * 4 + k) * 16 * WO_PITCH, wf[p * 4 + k][0], wf[p * 4 + k][1], wf[p * 4 + k][2], wf[p * 4 + k][3]);
        }
        TS(13);
        if (real) mbar_wait(bar_xo, 0);
        TS(12);
        float ya[4] = {0.f, 0.f, 0.f, 0.f}, yb[4] = {0.f, 0.f, 0.f, 0.f}, yc[4] = {0.f, 0.f, 0.f, 0.f}, yd[4] = {0.f, 0.f, 0.f, 0.f};
        const uint32_t oa = sb + SM_XO + (g & 3) * OS_PITCH + t * 8;
        #pragma unroll
        for (int k = 0; k < 8; k += 2) {
            const uint2 b0 = lds64(oa + k * 32), b1 = lds64(oa + k * 32 + 32);
            mma16816(ya, wf[k][0], wf[k][1], wf[k][2], wf[k][3], b0.x, b0.y);
            mma16816(yb, wf[k + 1][0], wf[k + 1][1], wf[k + 1][2], wf[k + 1][3], b1.x, b1.y);
        }
        #pragma unroll
        for (int k = 8; k < 12; k += 2) {
            const uint2 b0 = lds64(oa + k * 32), b1 = lds64(oa + k * 32 + 32);
            mma16816(yc, wf[k][0], wf[k][1], wf[k][2], wf[k][3], b0.x, b0.y);
            mma16816(yd, wf[k + 1][0], wf[k + 1][1], wf[k + 1][2], wf[k + 1][3], b1.x, b1.y);
        }
        float c00, c01, c10, c11;
        {
            const float4 u = *reinterpret_cast<const float4*>(smem + SM_XML + (t & 1) * 32);
            const float4 v = *reinterpret_cast<const float4*>(smem + SM_XML + (t & 1) * 32 + 16);
            const float M0 = fmaxf(u.x, v.x), M1 = fmaxf(u.z, v.z);
            const float e00 = ex2(u.x - M0), e01 = ex2(v.x - M0), e10 = ex2(u.z - M1), e11 = ex2(v.z - M1);
            const float r0 = __fdividef(1.f, fmaf(e00, u.y, e01 * v.y)), r1 = __fdividef(1.f, fmaf(e10, u.w, e11 * v.w));
            c00 = e00 * r0; c01 = e01 * r0; c10 = e10 * r1; c11 = e11 * r1;
        }
        TS(5);
        if (real) mbar_wait(bar_wo + 8 * (WO_PIECES - 1), 0);
        TS(6);
        #pragma unroll
        for (int k = 12; k < 16; k++) ldsm4t(wa + k * 16 * WO_PITCH, wf[k][0], wf[k][1], wf[k][2], wf[k][3]);
        #pragma unroll
        for (int k = 12; k < 16; k += 2) {
            const uint2 b0 = lds64(oa + k * 32), b1 = lds64(oa + k * 32 + 32);
            mma16816(yc, wf[k][0], wf[k][1], wf[k][2], wf[k][3], b0.x, b0.y);
            mma16816(yd, wf[k + 1][0], wf[k + 1][1], wf[k + 1][2], wf[k + 1][3], b1.x, b1.y);
        }
        {
            const float y_lo = fmaf(c00, ya[0] + yb[0], c01 * (ya[1] + yb[1])) + fmaf(c10, yc[0] + yd[0], c11 * (yc[1] + yd[1]));
            const float y_hi = fmaf(c00, ya[2] + yb[2], c01 * (ya[3] + yb[3])) + fmaf(c10, yc[2] + yd[2], c11 * (yc[3] + yd[3]));
            unsigned long long* yp = &g_y[hkv * (2 * D_MODEL) + (t & 1) * D_MODEL + rank * 144 + w9 * 16 + g];
            const bool pr = real && t < 2;
            ll_store(yp, __float_as_uint(y_lo), epoch, pr);
            ll_store(yp + 8, __float_as_uint(y_hi), epoch, pr);
        }
        if (tid == 0) asm volatile("red.relaxed.gpu.global.add.u32 [%0], 1;" :: "l"(&g_cnt) : "memory");
        TS(7);
        const int task = cta + 64 * w9;
        if (task < 144) {
            if (lane == 0 && real) {
                const uint32_t target = epoch * CNT_PER_LAUNCH - HINT_SLACK;
                uint32_t c; int it = 0;
                do { asm volatile("ld.relaxed.gpu.global.u32 %0, [%1];" : "=r"(c) : "l"(&g_cnt) : "memory"); } while ((int)(c - target) < 0 && ++it < 4096);
            }
            __syncwarp();
            TS(14);
            const int n0 = task * 8 + (lane >> 4) * 4;
            const unsigned long long* yp = &g_y[(lane & 15) * (2 * D_MODEL) + n0];
            uint32_t f[4], e[4]; int it = 0; bool ok;
            do {
                ll_load4(yp, f, e, real);
                ok = (e[0] == epoch && e[1] == epoch && e[2] == epoch && e[3] == epoch) || !real;
            } while (!ok && ++it < SPIN_LIMIT);
            __syncwarp();
            const float f0 = __uint_as_float(f[0]), f1 = __uint_as_float(f[1]), f2 = __uint_as_float(f[2]), f3 = __uint_as_float(f[3]);
            const bool l0 = lane & 1, l1 = lane & 2;
            const float p0 = (l0 ? f2 : f0) + __shfl_xor_sync(0xffffffffu, l0 ? f0 : f2, 1);
            const float p1 = (l0 ? f3 : f1) + __shfl_xor_sync(0xffffffffu, l0 ? f1 : f3, 1);
            float s = (l1 ? p1 : p0) + __shfl_xor_sync(0xffffffffu, l1 ? p0 : p1, 2);
            s += __shfl_xor_sync(0xffffffffu, s, 4);
            s += __shfl_xor_sync(0xffffffffu, s, 8);
            if ((lane & 12) == 0 && real) out[n0 + (l0 ? 2 : 0) + (l1 ? 1 : 0)] = __float2bfloat16(s);
        }
        TS(8);
        TS_DUMP;
    }
}

typedef CUresult (*EncodeFn)(CUtensorMap*, CUtensorMapDataType, cuuint32_t, void*, const cuuint64_t*, const cuuint64_t*,
                             const cuuint32_t*, const cuuint32_t*, CUtensorMapInterleave, CUtensorMapSwizzle,
                             CUtensorMapL2promotion, CUtensorMapFloatOOBfill);
}

extern "C" void kernel_launch(void* const* d_in, const int* in_sizes, int n_in, void* d_out, int out_size) {
    (void)in_sizes; (void)n_in; (void)out_size;
    static CUtensorMap wo_map;
    static const void* mapped = nullptr;
    if (mapped != d_in[4]) {
        void* fn = nullptr; cudaDriverEntryPointQueryResult qr;
        cudaGetDriverEntryPoint("cuTensorMapEncodeTiled", &fn, cudaEnableDefault, &qr);
        cuuint64_t dims[2] = {(cuuint64_t)D_MODEL, (cuuint64_t)NQ};
        cuuint64_t strides[1] = {(cuuint64_t)D_MODEL * 2};
        cuuint32_t box[2] = {152, 64}; cuuint32_t es[2] = {1, 1};
        ((EncodeFn)fn)(&wo_map, CU_TENSOR_MAP_DATA_TYPE_BFLOAT16, 2, d_in[4], dims, strides, box, es,
                       CU_TENSOR_MAP_INTERLEAVE_NONE, CU_TENSOR_MAP_SWIZZLE_NONE, CU_TENSOR_MAP_L2_PROMOTION_L2_128B,
                       CU_TENSOR_MAP_FLOAT_OOB_FILL_NONE);
        cudaFuncSetAttribute(fused_decode_kernel, cudaFuncAttributeMaxDynamicSharedMemorySize, SM_TOTAL);
        mapped = d_in[4];
    }
    fused_decode_kernel<<<NCTA, NTHREADS, SM_TOTAL, cudaStreamPerThread>>>(
        (const __nv_bfloat16*)d_in[0], (const __nv_bfloat16*)d_in[1], (const __nv_bfloat16*)d_in[2],
        (const __nv_bfloat16*)d_in[3], (__nv_bfloat16*)d_out, wo_map);
}
```

```cpp
#include <cuda_runtime.h>
#include <cuda_bf16.h>
#include <cuda.h>
#include <stdint.h>

#define WINDOW 12
#define WO_PACE (PACE_NS * WO_PIECE / CHUNK)
#define PACE_NS 334
#define PACE_T0 500
#define HINT_SLACK 16
#define EPOCH_CHUNK 44

namespace {

constexpr int D_MODEL = 576;
constexpr int NQ      = 4096;
constexpr int SK      = 32768;
constexpr int WIN     = 4096;
constexpr int NCTA    = 64;
constexpr int NTHREADS = 288;
constexpr int NSLOT   = 13;
constexpr int CHUNK   = 16384;
constexpr int NSTAGE  = 16;
constexpr int NCHUNK  = NSTAGE * 4;
constexpr int WO_PIECES = 4;
constexpr int WO_PITCH = 304;
constexpr int WO_PIECE = 64 * WO_PITCH;
constexpr int OS_PITCH = 544;
constexpr int CNT_PER_LAUNCH = NCTA;

constexpr int WQ_SLOT0 = 8;
constexpr int SM_RING = 0;
constexpr int SM_WQ   = WQ_SLOT0 * CHUNK;
constexpr int SM_QRED = SM_WQ + 576 * 128;
constexpr int SM_WO   = 0;
constexpr int SM_RED  = NSLOT * CHUNK;
constexpr int SM_XO   = SM_RED + 8192;
constexpr int SM_XML  = SM_XO + 4 * OS_PITCH;
constexpr int SM_QS   = SM_XML + 64;
constexpr int SM_M    = SM_QS + 512;
constexpr int SM_L    = SM_M + 96;
constexpr int SM_BAR  = SM_L + 96;
constexpr int SM_TOTAL = SM_BAR + 16 * NSLOT + 48;
static_assert(SM_QRED + 4096 <= NSLOT * CHUNK && WO_PIECES * WO_PIECE <= 5 * CHUNK, "smem map");

constexpr float SCALE_LOG2 = 0.08838834764831845f * 1.4426950408889634f;
constexpr int SPIN_LIMIT = 1 << 20;

__device__ unsigned int g_cnt;
__device__ unsigned long long g_y[16 * 2 * D_MODEL];
#define STAMP(cond, i)

__device__ __forceinline__ long long gtime() { long long t; asm volatile("mov.u64 %0, %globaltimer;" : "=l"(t)); return t; }
__device__ __forceinline__ uint32_t smem_u32(const void* p) { return (uint32_t)__cvta_generic_to_shared(p); }
__device__ __forceinline__ void mbar_init(uint32_t bar, uint32_t cnt) {
    asm volatile("mbarrier.init.shared::cta.b64 [%0], %1;" :: "r"(bar), "r"(cnt) : "memory");
}
__device__ __forceinline__ void mbar_expect_tx(uint32_t bar, uint32_t bytes) {
    asm volatile("mbarrier.arrive.expect_tx.shared::cta.b64 _, [%0], %1;" :: "r"(bar), "r"(bytes) : "memory");
}
__device__ __forceinline__ void mbar_arrive(uint32_t bar) {
    asm volatile("mbarrier.arrive.shared::cta.b64 _, [%0];" :: "r"(bar) : "memory");
}
__device__ __forceinline__ void mbar_wait(uint32_t bar, uint32_t parity) {
    uint32_t ok;
    int it = 0;
    do {
        asm volatile("{\n.reg .pred p;\nmbarrier.try_wait.parity.shared::cta.b64 p, [%1], %2;\nselp.u32 %0, 1, 0, p;\n}"
                     : "=r"(ok) : "r"(bar), "r"(parity) : "memory");
    } while (!ok && ++it < SPIN_LIMIT);
}
__device__ __forceinline__ bool mbar_test(uint32_t bar, uint32_t parity) {
    uint32_t ok;
    asm volatile("{\n.reg .pred p;\nmbarrier.test_wait.parity.shared::cta.b64 p, [%1], %2;\nselp.u32 %0, 1, 0, p;\n}"
                 : "=r"(ok) : "r"(bar), "r"(parity) : "memory");
    return __all_sync(0xffffffffu, ok != 0);
}
__device__ __forceinline__ void mbar_wait_cluster(uint32_t bar, uint32_t parity) {
    uint32_t ok;
    int it = 0;
    do {
        asm volatile("{\n.reg .pred p;\nmbarrier.try_wait.parity.shared::cta.b64 p, [%1], %2;\nselp.u32 %0, 1, 0, p;\n}"
                     : "=r"(ok) : "r"(bar), "r"(parity) : "memory");
    } while (!ok && ++it < SPIN_LIMIT);
}
__device__ __forceinline__ uint32_t mapa(uint32_t addr, uint32_t rank) {
    uint32_t r; asm("mapa.shared::cluster.u32 %0, %1, %2;" : "=r"(r) : "r"(addr), "r"(rank)); return r;
}
__device__ __forceinline__ void st_async_b32(uint32_t raddr, uint32_t v, uint32_t rbar, bool pr) {
    asm volatile("{\n.reg .pred q;\nsetp.ne.u32 q, %3, 0;\n@q st.async.weak.shared::cluster.mbarrier::complete_tx::bytes.b32 [%0], %1, [%2];\n}"
                 :: "r"(raddr), "r"(v), "r"(rbar), "r"((uint32_t)pr) : "memory");
}
__device__ __forceinline__ void cp_async16(uint32_t dst, const void* src) {
    asm volatile("cp.async.cg.shared.global [%0], [%1], 16;" :: "r"(dst), "l"(src) : "memory");
}
__device__ __forceinline__ uint2 lds64(uint32_t addr) {
    uint2 v; asm volatile("ld.shared.v2.u32 {%0,%1}, [%2];" : "=r"(v.x), "=r"(v.y) : "r"(addr)); return v;
}
__device__ __forceinline__ uint32_t lds32(uint32_t addr) {
    uint32_t v; asm volatile("ld.shared.u32 %0, [%1];" : "=r"(v) : "r"(addr)); return v;
}
__device__ __forceinline__ void ldsm4t(uint32_t addr, uint32_t& a0, uint32_t& a1, uint32_t& a2, uint32_t& a3) {
    asm volatile("ldmatrix.sync.aligned.m8n8.x4.trans.shared.b16 {%0,%1,%2,%3}, [%4];"
                 : "=r"(a0), "=r"(a1), "=r"(a2), "=r"(a3) : "r"(addr));
}
__device__ __forceinline__ void bulk_g2s(uint32_t dst, const void* src, uint32_t bytes, uint32_t bar, uint64_t pol) {
    asm volatile("cp.async.bulk.shared::cluster.global.mbarrier::complete_tx::bytes.L2::cache_hint [%0], [%1], %2, [%3], %4;"
                 :: "r"(dst), "l"(src), "r"(bytes), "r"(bar), "l"(pol) : "memory");
}
__device__ __forceinline__ void tma2d_g2s(uint32_t dst, const CUtensorMap* map, int c0, int c1, uint32_t bar, uint64_t pol) {
    asm volatile("cp.async.bulk.tensor.2d.shared::cluster.global.mbarrier::complete_tx::bytes.L2::cache_hint [%0], [%1, {%2, %3}], [%4], %5;"
                 :: "r"(dst), "l"(map), "r"(c0), "r"(c1), "r"(bar), "l"(pol) : "memory");
}
__device__ __forceinline__ uint4 ldg_stream(const void* p) {
    uint4 v;
    asm volatile("ld.global.nc.L1::no_allocate.v4.u32 {%0,%1,%2,%3}, [%4];" : "=r"(v.x), "=r"(v.y), "=r"(v.z), "=r"(v.w) : "l"(p));
    return v;
}
__device__ __forceinline__ uint4 lds128(uint32_t addr) {
    uint4 v;
    asm volatile("ld.shared.v4.u32 {%0,%1,%2,%3}, [%4];" : "=r"(v.x), "=r"(v.y), "=r"(v.z), "=r"(v.w) : "r"(addr));
    return v;
}
__device__ __forceinline__ void ll_store(unsigned long long* p, uint32_t payload, uint32_t epoch, bool pr) {
    asm volatile("{\n.reg .pred q;\n.reg .b64 v;\nsetp.ne.u32 q, %3, 0;\nmov.b64 v, {%1, %2};\n@q st.relaxed.gpu.global.b64 [%0], v;\n}"
                 :: "l"(p), "r"(payload), "r"(epoch), "r"((uint32_t)pr) : "memory");
}
__device__ __forceinline__ void ll_load4(const unsigned long long* p, uint32_t (&f)[4], uint32_t (&e)[4], bool pr) {
    asm volatile("{\n.reg .pred q;\n.reg .b64 a, b, c, d;\nsetp.ne.u32 q, %9, 0;\n"
                 "mov.b64 a, 0;\nmov.b64 b, 0;\nmov.b64 c, 0;\nmov.b64 d, 0;\n"
                 "@q ld.relaxed.gpu.global.v2.b64 {a, b}, [%8];\n@q ld.relaxed.gpu.global.v2.b64 {c, d}, [%8+16];\n"
                 "mov.b64 {%0, %4}, a;\nmov.b64 {%1, %5}, b;\nmov.b64 {%2, %6}, c;\nmov.b64 {%3, %7}, d;\n}"
                 : "=r"(f[0]), "=r"(f[1]), "=r"(f[2]), "=r"(f[3]), "=r"(e[0]), "=r"(e[1]), "=r"(e[2]), "=r"(e[3])
                 : "l"(p), "r"((uint32_t)pr) : "memory");
}
__device__ __forceinline__ void mma16816(float (&c)[4], uint32_t a0, uint32_t a1, uint32_t a2, uint32_t a3, uint32_t b0, uint32_t b1) {
    asm volatile("mma.sync.aligned.m16n8k16.row.col.f32.bf16.bf16.f32 {%0,%1,%2,%3}, {%4,%5,%6,%7}, {%8,%9}, {%0,%1,%2,%3};"
                 : "+f"(c[0]), "+f"(c[1]), "+f"(c[2]), "+f"(c[3])
                 : "r"(a0), "r"(a1), "r"(a2), "r"(a3), "r"(b0), "r"(b1));
}
__device__ __forceinline__ void mma1688(float (&c)[4], uint32_t a0, uint32_t a1, uint32_t b0) {
    asm volatile("mma.sync.aligned.m16n8k8.row.col.f32.bf16.bf16.f32 {%0,%1,%2,%3}, {%4,%5}, {%6}, {%0,%1,%2,%3};"
                 : "+f"(c[0]), "+f"(c[1]), "+f"(c[2]), "+f"(c[3]) : "r"(a0), "r"(a1), "r"(b0));
}
__device__ __forceinline__ float ex2(float x) { float y; asm("ex2.approx.ftz.f32 %0, %1;" : "=f"(y) : "f"(x)); return y; }
__device__ __forceinline__ uint32_t pack_bf16(float lo, float hi) {
    uint32_t r; asm("cvt.rn.bf16x2.f32 %0, %1, %2;" : "=r"(r) : "f"(hi), "f"(lo)); return r;
}
__device__ __forceinline__ float bf_lo(uint32_t v) { return __uint_as_float(v << 16); }
__device__ __forceinline__ float bf_hi(uint32_t v) { return __uint_as_float(v & 0xffff0000u); }
__device__ __forceinline__ int f2ord(float f) { int i = __float_as_int(f); return i ^ ((i >> 31) & 0x7fffffff); }
__device__ __forceinline__ float ord2f(int i) { return __int_as_float(i ^ ((i >> 31) & 0x7fffffff)); }
__device__ __forceinline__ void bar_sync(int id, int n) { asm volatile("bar.sync %0, %1;" :: "r"(id), "r"(n) : "memory"); }
__device__ __forceinline__ void bar_arrive(int id, int n) { asm volatile("bar.arrive %0, %1;" :: "r"(id), "r"(n) : "memory"); }
__device__ __forceinline__ bool elect_one() {
    uint32_t p;
    asm volatile("{\n.reg .pred q;\nelect.sync _|q, 0xffffffff;\nselp.u32 %0, 1, 0, q;\n}" : "=r"(p));
    return p != 0;
}
__device__ __forceinline__ void cluster_arrive_release() { asm volatile("barrier.cluster.arrive.release.aligned;" ::: "memory"); }
__device__ __forceinline__ void cluster_arrive_relaxed() { asm volatile("barrier.cluster.arrive.relaxed.aligned;" ::: "memory"); }
__device__ __forceinline__ void cluster_wait() { asm volatile("barrier.cluster.wait.acquire.aligned;" ::: "memory"); }

__global__ void __cluster_dims__(4, 1, 1) __launch_bounds__(NTHREADS, 1)
fused_decode_kernel(const __nv_bfloat16* __restrict__ x, const __nv_bfloat16* __restrict__ kc,
                    const __nv_bfloat16* __restrict__ vc, const __nv_bfloat16* __restrict__ wq,
                    __nv_bfloat16* __restrict__ out, const __grid_constant__ CUtensorMap wo_map)
{
    extern __shared__ __align__(1024) unsigned char smem[];
    const uint32_t sb = smem_u32(smem);
    const int tid = threadIdx.x, lane = tid & 31;
    const int warp = __shfl_sync(0xffffffffu, tid >> 5, 0);
    const int cta = blockIdx.x;
    const int hkv = cta >> 2, rank = cta & 3, bb = rank >> 1, split = rank & 1;
    const int g = lane >> 2, t = lane & 3;
    const uint32_t bar_full = sb + SM_BAR, bar_empty = bar_full + 8 * NSLOT;
    const uint32_t bar_wo = bar_empty + 8 * NSLOT, bar_xq = bar_wo + 32, bar_xo = bar_wo + 40;
    uint32_t epoch = 0;

    if (warp == 8) {
        const long long t_start = gtime();
        if (elect_one()) {
            const unsigned char* pf = reinterpret_cast<const unsigned char*>(wq) + (size_t)cta * 9 * NQ * 2;
            #pragma unroll
            for (int i = 0; i < 9; i++) asm volatile("cp.async.bulk.prefetch.L2.global [%0], %1;" :: "l"(pf + i * 8192), "r"(8192) : "memory");
        }
        if (elect_one()) {
            #pragma unroll
            for (int i = 0; i < NSLOT; i++) { mbar_init(bar_full + 8 * i, 1); mbar_init(bar_empty + 8 * i, 4); }
            #pragma unroll
            for (int i = 0; i < WO_PIECES; i++) mbar_init(bar_wo + 8 * i, 1);
            mbar_init(bar_xq, 1); mbar_init(bar_xo, 1);
            mbar_expect_tx(bar_xq, 512);
            mbar_expect_tx(bar_xo, 4 * (512 + 16));
            asm volatile("fence.mbarrier_init.release.cluster;" ::: "memory");
            asm volatile("prefetch.tensormap [%0];" :: "l"(&wo_map) : "memory");
        }
        __syncwarp();
        cluster_arrive_relaxed();
        bar_arrive(1, NTHREADS);
        {
            uint64_t pol; asm volatile("createpolicy.fractional.L2::evict_first.b64 %0, 1.0;" : "=l"(pol));
            const size_t row0 = (size_t)(bb * 16 + hkv) * SK + (SK - WIN) + split * 128;
            const unsigned char* kp = reinterpret_cast<const unsigned char*>(kc) + row0 * 256;
            const unsigned char* vp = reinterpret_cast<const unsigned char*>(vc) + row0 * 256;
            long long t_next = t_start + PACE_T0;
            uint32_t slot = 0, pass = 0;
            uint32_t lslot = 0, lph = 0;
            #pragma unroll 1
            for (int i = 0; i < NCHUNK; i++) {
                if (i >= WINDOW) {
                    mbar_wait(bar_full + 8 * lslot, lph);
                    if (++lslot == NSLOT) { lslot = 0; lph ^= 1; }
                }
                mbar_wait(bar_empty + 8 * slot, (pass ^ (slot < WQ_SLOT0 ? 1 : 0)) & 1);
                while (gtime() < t_next) ;
                t_next += PACE_NS;
                if (elect_one()) {
                    mbar_expect_tx(bar_full + 8 * slot, CHUNK);
                    bulk_g2s(sb + SM_RING + slot * CHUNK, ((i & 2) ? vp : kp) + (i & 1) * CHUNK, CHUNK, bar_full + 8 * slot, pol);
                }
                if ((i & 3) == 3) { kp += 4 * CHUNK; vp += 4 * CHUNK; }
                if (++slot == NSLOT) { slot = 0; pass ^= 1; }
                if (i == EPOCH_CHUNK) epoch = __ldcg(&g_cnt) / CNT_PER_LAUNCH + 1;
            }
            mbar_wait(bar_empty + 0, 0);
            #pragma unroll 1
            for (int p = 0; p < WO_PIECES; p++) {
                mbar_wait(bar_full + 8 * lslot, lph);
                if (++lslot == NSLOT) { lslot = 0; lph ^= 1; }
                mbar_wait(bar_empty + 8 * (p + 1), 0);
                while (gtime() < t_next) ;
                t_next += WO_PACE;
                if (elect_one()) {
                    mbar_expect_tx(bar_wo + 8 * p, WO_PIECE);
                    tma2d_g2s(sb + SM_WO + p * WO_PIECE, &wo_map, rank * 144, hkv * 256 + p * 64, bar_wo + 8 * p, pol);
                }
            }
        }
        cluster_wait();
        bar_sync(2, NTHREADS);
        if (lane < 4) {
            const int h = lane >> 1;
            const float* sm = reinterpret_cast<const float*>(smem + SM_M) + h;
            const float* sl = reinterpret_cast<const float*>(smem + SM_L) + h;
            float M = sm[0];
            #pragma unroll
            for (int w = 1; w < 8; w++) M = fmaxf(M, sm[2 * w]);
            float L = 0.f;
            #pragma unroll
            for (int w = 0; w < 8; w++) L = fmaf(ex2(sm[2 * w] - M), sl[2 * w], L);
            const float v = (lane & 1) ? L : M;
            #pragma unroll
            for (int r = 0; r < 4; r++)
                st_async_b32(mapa(sb + SM_XML + (rank * 4 + lane) * 4, r), __float_as_uint(v), mapa(bar_xo, r), true);
        }
        __syncwarp();
    } else {
        {
            const uint32_t wq_w = sb + SM_WQ + warp * (72 * 128);
            {
                const int rr = lane >> 3, ch = lane & 7;
                const uint32_t d0 = wq_w + rr * 128 + ((ch ^ rr) << 4), d1 = wq_w + (4 + rr) * 128 + ((ch ^ (4 + rr)) << 4);
                const unsigned char* src = reinterpret_cast<const unsigned char*>(wq) + (size_t)(warp * 72 + rr) * (NQ * 2) + cta * 128 + ch * 16;
                #pragma unroll
                for (int i = 0; i < 18; i++) {
                    cp_async16(((i & 1) ? d1 : d0) + (i >> 1) * 1024, src + (size_t)i * 4 * NQ * 2);
                    if ((i & 3) == 3 || i == 17) asm volatile("cp.async.commit_group;" ::: "memory");
                }
            }
            uint32_t xb[9];
            {
                const uint32_t* xw = reinterpret_cast<const uint32_t*>(x + (g & 1) * D_MODEL + warp * 72) + t;
                #pragma unroll
                for (int i = 0; i < 9; i++) xb[i] = __ldg(xw + i * 4);
            }
            epoch = __ldcg(&g_cnt) / CNT_PER_LAUNCH + 1;
            cluster_arrive_relaxed();
            bar_sync(1, NTHREADS);
            cluster_wait();
            float c[4][4];
            #pragma unroll
            for (int m = 0; m < 4; m++) { c[m][0] = c[m][1] = c[m][2] = c[m][3] = 0.f; }
            const uint32_t wa = wq_w + ((lane & 7) + ((lane >> 4) & 1) * 8) * 128;
            const uint32_t sw = (lane >> 3) & 1, l7 = lane & 7;
            #pragma unroll
            for (int k = 0; k < 4; k++) {
                if (k == 0) asm volatile("cp.async.wait_group 4;" ::: "memory");
                if (k == 1) asm volatile("cp.async.wait_group 3;" ::: "memory");
                if (k == 2) asm volatile("cp.async.wait_group 2;" ::: "memory");
                if (k == 3) asm volatile("cp.async.wait_group 1;" ::: "memory");
                __syncwarp();
                #pragma unroll
                for (int m = 0; m < 4; m++) {
                    uint32_t a0, a1, a2, a3;
                    ldsm4t(wa + k * 2048 + (((2 * m + sw) ^ l7) << 4), a0, a1, a2, a3);
                    mma16816(c[m], a0, a1, a2, a3, xb[2 * k], xb[2 * k + 1]);
                }
            }
            asm volatile("cp.async.wait_group 0;" ::: "memory");
            __syncwarp();
            {
                const uint32_t wt = wq_w + (64 + l7) * 128;
                #pragma unroll
                for (int m = 0; m < 4; m += 2) {
                    uint32_t a0, a1, a2, a3;
                    ldsm4t(wt + (((2 * m + (lane >> 3)) ^ l7) << 4), a0, a1, a2, a3);
                    mma1688(c[m], a0, a1, xb[8]);
                    mma1688(c[m + 1], a2, a3, xb[8]);
                }
            }
            {
                float* qr = reinterpret_cast<float*>(smem + SM_QRED) + warp * 128 + t * 16 + g;
                const float v0 = t == 0 ? c[0][0] : t == 1 ? c[1][0] : t == 2 ? c[2][0] : c[3][0];
                const float v1 = t == 0 ? c[0][1] : t == 1 ? c[1][1] : t == 2 ? c[2][1] : c[3][1];
                const float v2 = t == 0 ? c[0][2] : t == 1 ? c[1][2] : t == 2 ? c[2][2] : c[3][2];
                const float v3 = t == 0 ? c[0][3] : t == 1 ? c[1][3] : t == 2 ? c[2][3] : c[3][3];
                qr[0] = v0; qr[64] = v1; qr[8] = v2; qr[72] = v3;
            }
            bar_sync(5, 256);
            if (tid < 128) {
                const float* qr = reinterpret_cast<const float*>(smem + SM_QRED) + tid;
                float s = 0.f;
                #pragma unroll
                for (int w = 0; w < 8; w++) s += qr[w * 128];
                const float o = __shfl_xor_sync(0xffffffffu, s, 1);
                const uint32_t pk = (tid & 1) ? pack_bf16(o, s) : pack_bf16(s, o);
                const uint32_t dst = (tid >> 6) * 2 + (tid & 1);
                st_async_b32(mapa(sb + SM_QS + (rank * 64 + (tid & 62)) * 2, dst), pk, mapa(bar_xq, dst), true);
                asm volatile("fence.proxy.async.shared::cta;" ::: "memory");
                __syncwarp();
                if (lane == 0) {
                    #pragma unroll
                    for (int i = WQ_SLOT0; i < NSLOT; i++) mbar_arrive(bar_empty + 8 * i);
                }
            }
            mbar_wait(bar_xq, 0);
        }
        uint32_t qb[4][2];
        {
            const int hh = g & 1, par = (g >> 1) & 1, eta = g >> 2;
            #pragma unroll
            for (int j = 0; j < 4; j++) {
                const uint32_t a = sb + SM_QS + hh * 256 + (4 * (j ^ par) + t) * 16 + eta * 4;
                qb[j][0] = lds32(a); qb[j][1] = lds32(a + 8);
            }
        }

        float acc[8][4];
        #pragma unroll
        for (int e = 0; e < 8; e++) { acc[e][0] = acc[e][1] = acc[e][2] = acc[e][3] = 0.f; }
        float m0 = -INFINITY, m1 = -INFINITY, mown = -INFINITY, lsum = 0.f;
        const bool valid = ((t ^ g) & 1) == 0;
        const bool hi = t & 2;
        const uint32_t kc0 = sb + SM_RING + ((warp & 3) * 16 + g) * 256 + (4 * (g & 1) + t) * 16;
        const uint32_t voff = sb + SM_RING + ((warp & 3) * 16 + 2 * t) * 256 + ((g ^ (2 * t)) * 16);
        const int src0 = 4 * (2 * t) + 2 * (g & 1), src1 = 4 * (2 * t + 1) + 1 + 2 * (g & 1);
        const bool bsel = (g >> 1) == t;
        uint32_t slot = (warp >> 2) & 1, ph = 0;
        #pragma unroll 1
        for (int it = 0; it < NSTAGE; it++) {
            mbar_wait(bar_full + 8 * slot, ph);
            float ca[4] = {0.f, 0.f, 0.f, 0.f}, cb[4] = {0.f, 0.f, 0.f, 0.f};
            {
                uint4 ka[4], kh[4];
                #pragma unroll
                for (int j = 0; j < 4; j++) {
                    const uint32_t a = slot * CHUNK + ((kc0 ^ ((j & 1) * 64)) + (j >> 1) * 128);
                    ka[j] = lds128(a); kh[j] = lds128(a + 8 * 256);
                }
                #pragma unroll
                for (int j = 0; j < 4; j++) {
                    mma16816(ca, ka[j].x, ka[j].y, ka[j].z, ka[j].w, qb[j][0], qb[j][1]);
                    mma16816(cb, kh[j].x, kh[j].y, kh[j].z, kh[j].w, qb[j][0], qb[j][1]);
                }
            }
            __syncwarp();
            if (elect_one()) mbar_arrive(bar_empty + 8 * slot);
            slot += 2; if (slot >= NSLOT) { slot -= NSLOT; ph ^= 1; }
            const float sa = ((hi ? ca[3] : ca[0]) + __shfl_xor_sync(0xffffffffu, hi ? ca[2] : ca[1], 2)) * SCALE_LOG2;
            const float sb2 = ((hi ? cb[3] : cb[0]) + __shfl_xor_sync(0xffffffffu, hi ? cb[2] : cb[1], 2)) * SCALE_LOG2;
            const float mx = fmaxf(sa, sb2);
            if (__any_sync(0xffffffffu, valid && mx > mown)) {
                const int ko = f2ord(mx);
                const float n0 = fmaxf(m0, ord2f(__reduce_max_sync(0xffffffffu, (valid && !hi) ? ko : (int)0x80000000)));
                const float n1 = fmaxf(m1, ord2f(__reduce_max_sync(0xffffffffu, (valid && hi) ? ko : (int)0x80000000)));
                const float a0 = ex2(m0 - n0), a1 = ex2(m1 - n1);
                #pragma unroll
                for (int e = 0; e < 8; e++) { acc[e][0] *= a0; acc[e][1] *= a1; acc[e][2] *= a0; acc[e][3] *= a1; }
                lsum *= hi ? a1 : a0;
                m0 = n0; m1 = n1; mown = hi ? n1 : n0;
            }
            const float pa = ex2(sa - mown), pb = ex2(sb2 - mown);
            lsum += pa + pb;
            const uint32_t y = pack_bf16(pa, pb);
            uint32_t b0 = __shfl_sync(0xffffffffu, y, src0), b1 = __shfl_sync(0xffffffffu, y, src1);
            b0 = bsel ? b0 : 0u; b1 = bsel ? b1 : 0u;
            mbar_wait(bar_full + 8 * slot, ph);
            const uint32_t vb = slot * CHUNK + voff;
            const uint4 vA0 = lds128(vb), vB0 = lds128(vb + 128);
            const uint4 vA1 = lds128(vb + 8 * 256), vB1 = lds128(vb + 8 * 256 + 128);
            const uint4 vA2 = lds128(vb + 256), vB2 = lds128(vb + 256 + 128);
            const uint4 vA3 = lds128(vb + 9 * 256), vB3 = lds128(vb + 9 * 256 + 128);
            const uint32_t A0[4] = {vA0.x, vA0.y, vA0.z, vA0.w}, A1[4] = {vA1.x, vA1.y, vA1.z, vA1.w};
            const uint32_t A2[4] = {vA2.x, vA2.y, vA2.z, vA2.w}, A3[4] = {vA3.x, vA3.y, vA3.z, vA3.w};
            const uint32_t B0[4] = {vB0.x, vB0.y, vB0.z, vB0.w}, B1[4] = {vB1.x, vB1.y, vB1.z, vB1.w};
            const uint32_t B2[4] = {vB2.x, vB2.y, vB2.z, vB2.w}, B3[4] = {vB3.x, vB3.y, vB3.z, vB3.w};
            #pragma unroll
            for (int r = 0; r < 4; r++) {
                mma16816(acc[2 * r], __byte_perm(A0[r], A1[r], 0x5410), __byte_perm(B0[r], B1[r], 0x5410),
                         __byte_perm(A2[r], A3[r], 0x5410), __byte_perm(B2[r], B3[r], 0x5410), b0, b1);
                mma16816(acc[2 * r + 1], __byte_perm(A0[r], A1[r], 0x7632), __byte_perm(B0[r], B1[r], 0x7632),
                         __byte_perm(A2[r], A3[r], 0x7632), __byte_perm(B2[r], B3[r], 0x7632), b0, b1);
            }
            __syncwarp();
            if (elect_one()) mbar_arrive(bar_empty + 8 * slot);
            slot += 2; if (slot >= NSLOT) { slot -= NSLOT; ph ^= 1; }
        }
        const int ti = tid & 255;
        {
            const bool t1 = t & 2, t0 = t & 1;
            float h16[16];
            #pragma unroll
            for (int e = 0; e < 8; e++) {
                #pragma unroll
                for (int h = 0; h < 2; h++) {
                    const float s = t1 ? acc[e][h] : acc[e][2 + h];
                    const float k = t1 ? acc[e][2 + h] : acc[e][h];
                    h16[h * 8 + e] = k + __shfl_xor_sync(0xffffffffu, s, 18);
                }
            }
            float o8[8];
            #pragma unroll
            for (int e = 0; e < 8; e++) {
                const float s = t0 ? h16[e] : h16[8 + e];
                const float k = t0 ? h16[8 + e] : h16[e];
                o8[e] = k + __shfl_xor_sync(0xffffffffu, s, 9);
            }
            const int c = g ^ (2 * t);
            float* myred = reinterpret_cast<float*>(smem + SM_RED + warp * 1024);
            float4* dst = reinterpret_cast<float4*>(&myred[(t & 1) * 128 + (t >> 1) * 64 + c * 8]);
            dst[t1 ? 1 : 0] = t1 ? make_float4(o8[4], o8[5], o8[6], o8[7]) : make_float4(o8[0], o8[1], o8[2], o8[3]);
            dst[t1 ? 0 : 1] = t1 ? make_float4(o8[0], o8[1], o8[2], o8[3]) : make_float4(o8[4], o8[5], o8[6], o8[7]);
            float l = valid ? lsum : 0.f;
            l += __shfl_xor_sync(0xffffffffu, l, 5);
            l += __shfl_xor_sync(0xffffffffu, l, 8);
            l += __shfl_xor_sync(0xffffffffu, l, 16);
            if (lane == 0 || lane == 2) {
                reinterpret_cast<float*>(smem + SM_L)[warp * 2 + (lane >> 1)] = l;
                reinterpret_cast<float*>(smem + SM_M)[warp * 2 + (lane >> 1)] = mown;
            }
            bar_sync(2, NTHREADS);
            const float* sm = reinterpret_cast<const float*>(smem + SM_M) + (ti >> 7);
            float M = sm[0];
            #pragma unroll
            for (int w = 1; w < 8; w++) M = fmaxf(M, sm[2 * w]);
            float o = 0.f;
            #pragma unroll
            for (int w = 0; w < 8; w++) o = fmaf(ex2(sm[2 * w] - M), reinterpret_cast<const float*>(smem + SM_RED + w * 1024)[ti], o);
            const float on = __shfl_xor_sync(0xffffffffu, o, 1);
            const uint32_t pk = (ti & 1) ? pack_bf16(on, o) : pack_bf16(o, on);
            const int ke = ti & ~1;
            const uint32_t pos = (ke & ~15) + ((ke & 7) >> 1) * 4 + ((ke >> 3) & 1) * 2;
            const uint32_t la = sb + SM_XO + rank * OS_PITCH + pos * 2, r0 = (ti & 1) * 2;
            st_async_b32(mapa(la, r0), pk, mapa(bar_xo, r0), true);
            st_async_b32(mapa(la, r0 + 1), pk, mapa(bar_xo, r0 + 1), true);
        }
    }

    {
        const int w9 = warp;
        uint32_t wf[16][4];
        const uint32_t wa = sb + SM_WO + ((lane & 7) + ((lane >> 4) & 1) * 8) * WO_PITCH + (w9 * 16 + ((lane >> 3) & 1) * 8) * 2;
        #pragma unroll
        for (int p = 0; p < 2; p++) {
            mbar_wait(bar_wo + 8 * p, 0);
            #pragma unroll
            for (int k = 0; k < 4; k++) ldsm4t(wa + (p * 4 + k) * 16 * WO_PITCH, wf[p * 4 + k][0], wf[p * 4 + k][1], wf[p * 4 + k][2], wf[p * 4 + k][3]);
        }
        const bool have2 = mbar_test(bar_wo + 16, 0), have3 = have2 && mbar_test(bar_wo + 24, 0);
        if (have2) {
            #pragma unroll
            for (int k = 8; k < 12; k++) ldsm4t(wa + k * 16 * WO_PITCH, wf[k][0], wf[k][1], wf[k][2], wf[k][3]);
        }
        if (have3) {
            #pragma unroll
            for (int k = 12; k < 16; k++) ldsm4t(wa + k * 16 * WO_PITCH, wf[k][0], wf[k][1], wf[k][2], wf[k][3]);
        }
        mbar_wait(bar_xo, 0);
        float ya[4] = {0.f, 0.f, 0.f, 0.f}, yb[4] = {0.f, 0.f, 0.f, 0.f}, yc[4] = {0.f, 0.f, 0.f, 0.f}, yd[4] = {0.f, 0.f, 0.f, 0.f};
        const uint32_t oa = sb + SM_XO + (g & 3) * OS_PITCH + t * 8;
        uint2 bf[16];
        #pragma unroll
        for (int k = 0; k < 16; k++) bf[k] = lds64(oa + k * 32);
        const uint4 mu = lds128(sb + SM_XML + (t & 1) * 32), mv = lds128(sb + SM_XML + (t & 1) * 32 + 16);
        #pragma unroll
        for (int k = 0; k < 8; k += 2) {
            mma16816(ya, wf[k][0], wf[k][1], wf[k][2], wf[k][3], bf[k].x, bf[k].y);
            mma16816(yb, wf[k + 1][0], wf[k + 1][1], wf[k + 1][2], wf[k + 1][3], bf[k + 1].x, bf[k + 1].y);
        }
        float c00, c01, c10, c11;
        {
            const float m00 = __uint_as_float(mu.x), l00 = __uint_as_float(mu.y), m10 = __uint_as_float(mu.z), l10 = __uint_as_float(mu.w);
            const float m01 = __uint_as_float(mv.x), l01 = __uint_as_float(mv.y), m11 = __uint_as_float(mv.z), l11 = __uint_as_float(mv.w);
            const float M0 = fmaxf(m00, m01), M1 = fmaxf(m10, m11);
            const float e00 = ex2(m00 - M0), e01 = ex2(m01 - M0), e10 = ex2(m10 - M1), e11 = ex2(m11 - M1);
            const float r0 = __fdividef(1.f, fmaf(e00, l00, e01 * l01)), r1 = __fdividef(1.f, fmaf(e10, l10, e11 * l11));
            c00 = e00 * r0; c01 = e01 * r0; c10 = e10 * r1; c11 = e11 * r1;
        }
        if (!have2) {
            mbar_wait(bar_wo + 16, 0);
            #pragma unroll
            for (int k = 8; k < 12; k++) ldsm4t(wa + k * 16 * WO_PITCH, wf[k][0], wf[k][1], wf[k][2], wf[k][3]);
        }
        #pragma unroll
        for (int k = 8; k < 12; k += 2) {
            mma16816(yc, wf[k][0], wf[k][1], wf[k][2], wf[k][3], bf[k].x, bf[k].y);
            mma16816(yd, wf[k + 1][0], wf[k + 1][1], wf[k + 1][2], wf[k + 1][3], bf[k + 1].x, bf[k + 1].y);
        }
        if (!have3) {
            mbar_wait(bar_wo + 24, 0);
            #pragma unroll
            for (int k = 12; k < 16; k++) ldsm4t(wa + k * 16 * WO_PITCH, wf[k][0], wf[k][1], wf[k][2], wf[k][3]);
        }
        {
            float ye[4] = {0.f, 0.f, 0.f, 0.f}, yf[4] = {0.f, 0.f, 0.f, 0.f};
            mma16816(ye, wf[12][0], wf[12][1], wf[12][2], wf[12][3], bf[12].x, bf[12].y);
            mma16816(yf, wf[13][0], wf[13][1], wf[13][2], wf[13][3], bf[13].x, bf[13].y);
            mma16816(yc, wf[14][0], wf[14][1], wf[14][2], wf[14][3], bf[14].x, bf[14].y);
            mma16816(yd, wf[15][0], wf[15][1], wf[15][2], wf[15][3], bf[15].x, bf[15].y);
            #pragma unroll
            for (int i = 0; i < 4; i++) { yc[i] += ye[i]; yd[i] += yf[i]; }
        }
        {
            const float y_lo = fmaf(c00, ya[0] + yb[0], c01 * (ya[1] + yb[1])) + fmaf(c10, yc[0] + yd[0], c11 * (yc[1] + yd[1]));
            const float y_hi = fmaf(c00, ya[2] + yb[2], c01 * (ya[3] + yb[3])) + fmaf(c10, yc[2] + yd[2], c11 * (yc[3] + yd[3]));
            unsigned long long* yp = &g_y[hkv * (2 * D_MODEL) + (t & 1) * D_MODEL + rank * 144 + w9 * 16 + g];
            const bool pr = t < 2;
            ll_store(yp, __float_as_uint(y_lo), epoch, pr);
            ll_store(yp + 8, __float_as_uint(y_hi), epoch, pr);
        }
        if (tid == 0) asm volatile("red.relaxed.gpu.global.add.u32 [%0], 1;" :: "l"(&g_cnt) : "memory");
        const int task = cta + 64 * w9;
        if (task < 144) {
            if (lane == 0) {
                const uint32_t target = epoch * CNT_PER_LAUNCH - HINT_SLACK;
                uint32_t c; int it = 0;
                do { asm volatile("ld.relaxed.gpu.global.u32 %0, [%1];" : "=r"(c) : "l"(&g_cnt) : "memory"); } while ((int)(c - target) < 0 && ++it < 4096);
            }
            __syncwarp();
            const int n0 = task * 8 + (lane >> 4) * 4;
            const unsigned long long* yp = &g_y[(lane & 15) * (2 * D_MODEL) + n0];
            uint32_t f[4], e[4]; int it = 0; bool ok;
            do {
                ll_load4(yp, f, e, true);
                ok = e[0] == epoch && e[1] == epoch && e[2] == epoch && e[3] == epoch;
            } while (!ok && ++it < SPIN_LIMIT);
            __syncwarp();
            const float f0 = __uint_as_float(f[0]), f1 = __uint_as_float(f[1]), f2 = __uint_as_float(f[2]), f3 = __uint_as_float(f[3]);
            const bool l0 = lane & 1, l1 = lane & 2;
            const float p0 = (l0 ? f2 : f0) + __shfl_xor_sync(0xffffffffu, l0 ? f0 : f2, 1);
            const float p1 = (l0 ? f3 : f1) + __shfl_xor_sync(0xffffffffu, l0 ? f1 : f3, 1);
            float s = (l1 ? p1 : p0) + __shfl_xor_sync(0xffffffffu, l1 ? p0 : p1, 2);
            s += __shfl_xor_sync(0xffffffffu, s, 4);
            s += __shfl_xor_sync(0xffffffffu, s, 8);
            if ((lane & 12) == 0) out[n0 + (l0 ? 2 : 0) + (l1 ? 1 : 0)] = __float2bfloat16(s);
        }
    }
}

typedef CUresult (*EncodeFn)(CUtensorMap*, CUtensorMapDataType, cuuint32_t, void*, const cuuint64_t*, const cuuint64_t*,
                             const cuuint32_t*, const cuuint32_t*, CUtensorMapInterleave, CUtensorMapSwizzle,
                             CUtensorMapL2promotion, CUtensorMapFloatOOBfill);
}

extern "C" void kernel_launch(void* const* d_in, const int* in_sizes, int n_in, void* d_out, int out_size) {
    (void)in_sizes; (void)n_in; (void)out_size;
    static CUtensorMap wo_map;
    static const void* mapped = nullptr;
    if (mapped != d_in[4]) {
        void* fn = nullptr; cudaDriverEntryPointQueryResult qr;
        cudaGetDriverEntryPoint("cuTensorMapEncodeTiled", &fn, cudaEnableDefault, &qr);
        cuuint64_t dims[2] = {(cuuint64_t)D_MODEL, (cuuint64_t)NQ};
        cuuint64_t strides[1] = {(cuuint64_t)D_MODEL * 2};
        cuuint32_t box[2] = {152, 64}; cuuint32_t es[2] = {1, 1};
        ((EncodeFn)fn)(&wo_map, CU_TENSOR_MAP_DATA_TYPE_BFLOAT16, 2, d_in[4], dims, strides, box, es,
                       CU_TENSOR_MAP_INTERLEAVE_NONE, CU_TENSOR_MAP_SWIZZLE_NONE, CU_TENSOR_MAP_L2_PROMOTION_L2_128B,
                       CU_TENSOR_MAP_FLOAT_OOB_FILL_NONE);
        cudaFuncSetAttribute(fused_decode_kernel, cudaFuncAttributeMaxDynamicSharedMemorySize, SM_TOTAL);
        mapped = d_in[4];
    }
    fused_decode_kernel<<<NCTA, NTHREADS, SM_TOTAL, cudaStreamPerThread>>>(
        (const __nv_bfloat16*)d_in[0], (const __nv_bfloat16*)d_in[1], (const __nv_bfloat16*)d_in[2],
        (const __nv_bfloat16*)d_in[3], (__nv_bfloat16*)d_out, wo_map);
}
```

```cpp
#include <cuda_runtime.h>
#include <cuda_bf16.h>
#include <cuda.h>
#include <stdint.h>

#define WINDOW 12
#define WO_PACE (PACE_NS * WO_PIECE / CHUNK)
#define PACE_NS 335
#define PACE_T0 500
#define HELPER_SLEEP 500
#define ML_SEND_CHUNK 40
#define COEF_CHUNK 44

namespace {

constexpr int D_MODEL = 576;
constexpr int NQ      = 4096;
constexpr int SK      = 32768;
constexpr int WIN     = 4096;
constexpr int NCTA    = 64;
constexpr int NTHREADS = 320;
constexpr int NWORK = 288;
constexpr int NSLOT   = 13;
constexpr int CHUNK   = 16384;
constexpr int NSTAGE  = 16;
constexpr int NCHUNK  = NSTAGE * 4;
constexpr int WO_PIECES = 4;
constexpr int WO_PITCH = 304;
constexpr int WO_PIECE = 64 * WO_PITCH;
constexpr int OS_PITCH = 544;
constexpr int CNT_PER_LAUNCH = NCTA;

constexpr int WQ_SLOT0 = 8;
constexpr int SM_RING = 0;
constexpr int SM_WQ   = WQ_SLOT0 * CHUNK;
constexpr int SM_QRED = SM_WQ + 576 * 128;
constexpr int SM_WO   = 0;
constexpr int SM_SPR  = NSLOT * CHUNK;
constexpr int SM_XO   = SM_SPR + 8 * 2048;
constexpr int SM_QS   = SM_XO + 4 * OS_PITCH;
constexpr int SM_M    = SM_QS;
constexpr int SM_L    = SM_QS + 64;
constexpr int SM_COEF = SM_QS + 128;
constexpr int SM_XML  = SM_QS + 512;
constexpr int SM_BAR  = SM_XML + 16;
constexpr int SM_TOTAL = SM_BAR + 16 * NSLOT + 64;
static_assert(SM_TOTAL <= 232448, "smem size");
static_assert(SM_QRED + 4096 <= NSLOT * CHUNK && WO_PIECES * WO_PIECE <= 5 * CHUNK, "smem map");

constexpr float SCALE_LOG2 = 0.08838834764831845f * 1.4426950408889634f;
#define SPIN_LOG2 20
constexpr int SPIN_LIMIT = 1 << SPIN_LOG2;

__device__ unsigned int g_cnt;
__device__ float2 g_acc[2 * D_MODEL];

__device__ __forceinline__ long long gtime() { long long t; asm volatile("mov.u64 %0, %globaltimer;" : "=l"(t)); return t; }
__device__ __forceinline__ uint32_t smem_u32(const void* p) { return (uint32_t)__cvta_generic_to_shared(p); }
__device__ __forceinline__ void mbar_init(uint32_t bar, uint32_t cnt) {
    asm volatile("mbarrier.init.shared::cta.b64 [%0], %1;" :: "r"(bar), "r"(cnt) : "memory");
}
__device__ __forceinline__ void mbar_expect_tx(uint32_t bar, uint32_t bytes) {
    asm volatile("mbarrier.arrive.expect_tx.shared::cta.b64 _, [%0], %1;" :: "r"(bar), "r"(bytes) : "memory");
}
__device__ __forceinline__ void mbar_arrive(uint32_t bar) {
    asm volatile("mbarrier.arrive.shared::cta.b64 _, [%0];" :: "r"(bar) : "memory");
}
__device__ __forceinline__ void mbar_wait(uint32_t bar, uint32_t parity) {
    uint32_t ok;
    int it = 0;
    do {
        asm volatile("{\n.reg .pred p;\nmbarrier.try_wait.parity.shared::cta.b64 p, [%1], %2;\nselp.u32 %0, 1, 0, p;\n}"
                     : "=r"(ok) : "r"(bar), "r"(parity) : "memory");
    } while (!ok && ++it < SPIN_LIMIT);
}
__device__ __forceinline__ bool mbar_test(uint32_t bar, uint32_t parity) {
    uint32_t ok;
    asm volatile("{\n.reg .pred p;\nmbarrier.test_wait.parity.shared::cta.b64 p, [%1], %2;\nselp.u32 %0, 1, 0, p;\n}"
                 : "=r"(ok) : "r"(bar), "r"(parity) : "memory");
    return __all_sync(0xffffffffu, ok != 0);
}
__device__ __forceinline__ uint32_t mapa(uint32_t addr, uint32_t rank) {
    uint32_t r; asm("mapa.shared::cluster.u32 %0, %1, %2;" : "=r"(r) : "r"(addr), "r"(rank)); return r;
}
__device__ __forceinline__ void st_async_b32(uint32_t raddr, uint32_t v, uint32_t rbar, bool pr) {
    asm volatile("{\n.reg .pred q;\nsetp.ne.u32 q, %3, 0;\n@q st.async.weak.shared::cluster.mbarrier::complete_tx::bytes.b32 [%0], %1, [%2];\n}"
                 :: "r"(raddr), "r"(v), "r"(rbar), "r"((uint32_t)pr) : "memory");
}
__device__ __forceinline__ void cp_async16(uint32_t dst, const void* src) {
    asm volatile("cp.async.cg.shared.global [%0], [%1], 16;" :: "r"(dst), "l"(src) : "memory");
}
__device__ __forceinline__ uint2 lds64(uint32_t addr) {
    uint2 v; asm volatile("ld.shared.v2.u32 {%0,%1}, [%2];" : "=r"(v.x), "=r"(v.y) : "r"(addr)); return v;
}
__device__ __forceinline__ uint32_t lds32(uint32_t addr) {
    uint32_t v; asm volatile("ld.shared.u32 %0, [%1];" : "=r"(v) : "r"(addr)); return v;
}
__device__ __forceinline__ void ldsm4t(uint32_t addr, uint32_t& a0, uint32_t& a1, uint32_t& a2, uint32_t& a3) {
    asm volatile("ldmatrix.sync.aligned.m8n8.x4.trans.shared.b16 {%0,%1,%2,%3}, [%4];"
                 : "=r"(a0), "=r"(a1), "=r"(a2), "=r"(a3) : "r"(addr));
}
__device__ __forceinline__ void bulk_g2s(uint32_t dst, const void* src, uint32_t bytes, uint32_t bar, uint64_t pol) {
    asm volatile("cp.async.bulk.shared::cluster.global.mbarrier::complete_tx::bytes.L2::cache_hint [%0], [%1], %2, [%3], %4;"
                 :: "r"(dst), "l"(src), "r"(bytes), "r"(bar), "l"(pol) : "memory");
}
__device__ __forceinline__ void tma2d_g2s(uint32_t dst, const CUtensorMap* map, int c0, int c1, uint32_t bar, uint64_t pol) {
    asm volatile("cp.async.bulk.tensor.2d.shared::cluster.global.mbarrier::complete_tx::bytes.L2::cache_hint [%0], [%1, {%2, %3}], [%4], %5;"
                 :: "r"(dst), "l"(map), "r"(c0), "r"(c1), "r"(bar), "l"(pol) : "memory");
}
__device__ __forceinline__ uint4 lds128(uint32_t addr) {
    uint4 v;
    asm volatile("ld.shared.v4.u32 {%0,%1,%2,%3}, [%4];" : "=r"(v.x), "=r"(v.y), "=r"(v.z), "=r"(v.w) : "r"(addr));
    return v;
}
__device__ __forceinline__ void mma16816(float (&c)[4], uint32_t a0, uint32_t a1, uint32_t a2, uint32_t a3, uint32_t b0, uint32_t b1) {
    asm volatile("mma.sync.aligned.m16n8k16.row.col.f32.bf16.bf16.f32 {%0,%1,%2,%3}, {%4,%5,%6,%7}, {%8,%9}, {%0,%1,%2,%3};"
                 : "+f"(c[0]), "+f"(c[1]), "+f"(c[2]), "+f"(c[3])
                 : "r"(a0), "r"(a1), "r"(a2), "r"(a3), "r"(b0), "r"(b1));
}
__device__ __forceinline__ void mma1688(float (&c)[4], uint32_t a0, uint32_t a1, uint32_t b0) {
    asm volatile("mma.sync.aligned.m16n8k8.row.col.f32.bf16.bf16.f32 {%0,%1,%2,%3}, {%4,%5}, {%6}, {%0,%1,%2,%3};"
                 : "+f"(c[0]), "+f"(c[1]), "+f"(c[2]), "+f"(c[3]) : "r"(a0), "r"(a1), "r"(b0));
}
__device__ __forceinline__ float ex2(float x) { float y; asm("ex2.approx.ftz.f32 %0, %1;" : "=f"(y) : "f"(x)); return y; }
__device__ __forceinline__ uint32_t pack_bf16(float lo, float hi) {
    uint32_t r; asm("cvt.rn.bf16x2.f32 %0, %1, %2;" : "=r"(r) : "f"(hi), "f"(lo)); return r;
}
__device__ __forceinline__ int f2ord(float f) { int i = __float_as_int(f); return i ^ ((i >> 31) & 0x7fffffff); }
__device__ __forceinline__ float ord2f(int i) { return __int_as_float(i ^ ((i >> 31) & 0x7fffffff)); }
__device__ __forceinline__ void bar_sync(int id, int n) { asm volatile("bar.sync %0, %1;" :: "r"(id), "r"(n) : "memory"); }
__device__ __forceinline__ void bar_arrive(int id, int n) { asm volatile("bar.arrive %0, %1;" :: "r"(id), "r"(n) : "memory"); }
__device__ __forceinline__ bool elect_one() {
    uint32_t p;
    asm volatile("{\n.reg .pred q;\nelect.sync _|q, 0xffffffff;\nselp.u32 %0, 1, 0, q;\n}" : "=r"(p));
    return p != 0;
}
__device__ __forceinline__ void cluster_arrive_relaxed() { asm volatile("barrier.cluster.arrive.relaxed.aligned;" ::: "memory"); }
__device__ __forceinline__ void cluster_wait() { asm volatile("barrier.cluster.wait.acquire.aligned;" ::: "memory"); }

__global__ void __cluster_dims__(4, 1, 1) __launch_bounds__(NTHREADS, 1)
fused_decode_kernel(const __nv_bfloat16* __restrict__ x, const __nv_bfloat16* __restrict__ kc,
                    const __nv_bfloat16* __restrict__ vc, const __nv_bfloat16* __restrict__ wq,
                    __nv_bfloat16* __restrict__ out, const __grid_constant__ CUtensorMap wo_map)
{
    extern __shared__ __align__(1024) unsigned char smem[];
    const uint32_t sb = smem_u32(smem);
    const int tid = threadIdx.x, lane = tid & 31;
    const int warp = __shfl_sync(0xffffffffu, tid >> 5, 0);
    const int cta = blockIdx.x;
    const int hkv = cta >> 2, rank = cta & 3, bb = rank >> 1, split = rank & 1;
    const int g = lane >> 2, t = lane & 3;
    const uint32_t bar_full = sb + SM_BAR, bar_empty = bar_full + 8 * NSLOT;
    const uint32_t bar_wo = bar_empty + 8 * NSLOT, bar_xq = bar_wo + 32, bar_xo = bar_wo + 40;
    const uint32_t bar_l = bar_wo + 48, bar_ml = bar_wo + 56;

    if (warp == 9) {
        cluster_arrive_relaxed();
        bar_sync(1, NTHREADS);
        uint32_t c;
        asm volatile("ld.relaxed.gpu.global.u32 %0, [%1];" : "=r"(c) : "l"(&g_cnt) : "memory");
        const uint32_t target = (c / CNT_PER_LAUNCH + 1) * CNT_PER_LAUNCH;
        if (lane < 18) asm volatile("st.relaxed.gpu.global.v2.f32 [%0], {%1, %1};" :: "l"(&g_acc[cta * 18 + lane]), "f"(0.f) : "memory");
        __syncwarp();
        if (lane == 0) asm volatile("fence.acq_rel.gpu;\nred.relaxed.gpu.global.add.u32 [%0], 1;" :: "l"(&g_cnt) : "memory");
        __syncwarp();
        cluster_wait();
        if (lane == 0) {
            int it = 0;
            do {
                __nanosleep(HELPER_SLEEP);
                asm volatile("ld.acquire.gpu.global.u32 %0, [%1];" : "=r"(c) : "l"(&g_cnt) : "memory");
            } while ((int)(c - target) < 0 && ++it < SPIN_LIMIT);
            mbar_arrive(bar_l);
        }
        return;
    }
    if (warp == 8) {
        const long long t_start = gtime();
        if (elect_one()) {
            const unsigned char* pf = reinterpret_cast<const unsigned char*>(wq) + (size_t)cta * 9 * NQ * 2;
            #pragma unroll
            for (int i = 0; i < 9; i++) asm volatile("cp.async.bulk.prefetch.L2.global [%0], %1;" :: "l"(pf + i * 8192), "r"(8192) : "memory");
        }
        if (elect_one()) {
            #pragma unroll
            for (int i = 0; i < NSLOT; i++) { mbar_init(bar_full + 8 * i, 1); mbar_init(bar_empty + 8 * i, 4); }
            #pragma unroll
            for (int i = 0; i < WO_PIECES; i++) mbar_init(bar_wo + 8 * i, 1);
            mbar_init(bar_xq, 1); mbar_init(bar_xo, 1); mbar_init(bar_l, 9); mbar_init(bar_ml, 1);
            mbar_expect_tx(bar_xq, 512);
            mbar_expect_tx(bar_xo, 4 * 512);
            mbar_expect_tx(bar_ml, 16);
            asm volatile("fence.mbarrier_init.release.cluster;" ::: "memory");
            asm volatile("prefetch.tensormap [%0];" :: "l"(&wo_map) : "memory");
        }
        __syncwarp();
        cluster_arrive_relaxed();
        bar_arrive(1, NTHREADS);
        {
            uint64_t pol; asm volatile("createpolicy.fractional.L2::evict_first.b64 %0, 1.0;" : "=l"(pol));
            const size_t off0 = ((size_t)(bb * 16 + hkv) * SK + (SK - WIN) + split * 64) * 256;
            const unsigned char* src = reinterpret_cast<const unsigned char*>(kc) + off0;
            long long t_next = t_start + PACE_T0;
            uint32_t slot = 0, pass = 0;
            uint32_t lslot = 0, lph = 0;
            float ml_m = 0.f, ml_l = 0.f;
            #pragma unroll 1
            for (int i = 0; i < NCHUNK; i++) {
                if (i >= WINDOW) {
                    mbar_wait(bar_full + 8 * lslot, lph);
                    if (++lslot == NSLOT) { lslot = 0; lph ^= 1; }
                }
                mbar_wait(bar_empty + 8 * slot, (pass ^ (slot < WQ_SLOT0 ? 1 : 0)) & 1);
                while (gtime() < t_next) ;
                t_next += PACE_NS;
                if (elect_one()) {
                    mbar_expect_tx(bar_full + 8 * slot, CHUNK);
                    bulk_g2s(sb + SM_RING + slot * CHUNK, src, CHUNK, bar_full + 8 * slot, pol);
                }
                src += 2 * CHUNK;
                if (i == NCHUNK / 2 - 1) src = reinterpret_cast<const unsigned char*>(vc) + off0;
                if (++slot == NSLOT) { slot = 0; pass ^= 1; }
                if (i == ML_SEND_CHUNK) {
                    mbar_wait(bar_l, 0);
                    const float* sm = reinterpret_cast<const float*>(smem + SM_M) + (lane & 1);
                    const float* sl = reinterpret_cast<const float*>(smem + SM_L) + (lane & 1);
                    ml_m = sm[0];
                    #pragma unroll
                    for (int w = 1; w < 8; w++) ml_m = fmaxf(ml_m, sm[2 * w]);
                    ml_l = 0.f;
                    #pragma unroll
                    for (int w = 0; w < 8; w++) ml_l = fmaf(ex2(sm[2 * w] - ml_m), sl[2 * w], ml_l);
                    const float vm = __shfl_sync(0xffffffffu, ml_m, lane >> 1), vl = __shfl_sync(0xffffffffu, ml_l, lane >> 1);
                    st_async_b32(mapa(sb + SM_XML + (lane & 3) * 4, rank ^ 1), __float_as_uint((lane & 1) ? vl : vm), mapa(bar_ml, rank ^ 1), lane < 4);
                }
                if (i == COEF_CHUNK) {
                    mbar_wait(bar_ml, 0);
                    const int h = lane & 1, w = (lane >> 1) & 7;
                    const float pm = reinterpret_cast<const float*>(smem + SM_XML)[2 * h], pl = reinterpret_cast<const float*>(smem + SM_XML)[2 * h + 1];
                    const float M = fmaxf(ml_m, pm);
                    const float L = fmaf(ex2(ml_m - M), ml_l, ex2(pm - M) * pl);
                    const float cf = ex2(reinterpret_cast<const float*>(smem + SM_M)[2 * w + h] - M) * __fdividef(1.f, L);
                    if (lane < 16) reinterpret_cast<float*>(smem + SM_COEF)[h * 8 + w] = cf;
                    __syncwarp();
                    bar_arrive(2, NWORK);
                }
            }
            mbar_wait(bar_empty + 0, 0);
            #pragma unroll 1
            for (int p = 0; p < WO_PIECES; p++) {
                mbar_wait(bar_full + 8 * lslot, lph);
                if (++lslot == NSLOT) { lslot = 0; lph ^= 1; }
                mbar_wait(bar_empty + 8 * (p + 1), 0);
                while (gtime() < t_next) ;
                t_next += WO_PACE;
                if (elect_one()) {
                    mbar_expect_tx(bar_wo + 8 * p, WO_PIECE);
                    tma2d_g2s(sb + SM_WO + p * WO_PIECE, &wo_map, rank * 144, hkv * 256 + p * 64, bar_wo + 8 * p, pol);
                }
            }
        }
        cluster_wait();
    } else {
        {
            const uint32_t wq_w = sb + SM_WQ + warp * (72 * 128);
            {
                const int rr = lane >> 3, ch = lane & 7;
                const uint32_t d0 = wq_w + rr * 128 + ((ch ^ rr) << 4), d1 = wq_w + (4 + rr) * 128 + ((ch ^ (4 + rr)) << 4);
                const unsigned char* src = reinterpret_cast<const unsigned char*>(wq) + (size_t)(warp * 72 + rr) * (NQ * 2) + cta * 128 + ch * 16;
                #pragma unroll
                for (int i = 0; i < 18; i++) {
                    cp_async16(((i & 1) ? d1 : d0) + (i >> 1) * 1024, src + (size_t)i * 4 * NQ * 2);
                    if ((i & 3) == 3 || i == 17) asm volatile("cp.async.commit_group;" ::: "memory");
                }
            }
            uint32_t xb[9];
            {
                const uint32_t* xw = reinterpret_cast<const uint32_t*>(x + (g & 1) * D_MODEL + warp * 72) + t;
                #pragma unroll
                for (int i = 0; i < 9; i++) xb[i] = __ldg(xw + i * 4);
            }
            cluster_arrive_relaxed();
            bar_sync(1, NTHREADS);
            cluster_wait();
            float c[4][4];
            #pragma unroll
            for (int m = 0; m < 4; m++) { c[m][0] = c[m][1] = c[m][2] = c[m][3] = 0.f; }
            const uint32_t wa = wq_w + ((lane & 7) + ((lane >> 4) & 1) * 8) * 128;
            const uint32_t sw = (lane >> 3) & 1, l7 = lane & 7;
            #pragma unroll
            for (int k = 0; k < 4; k++) {
                if (k == 0) asm volatile("cp.async.wait_group 4;" ::: "memory");
                if (k == 1) asm volatile("cp.async.wait_group 3;" ::: "memory");
                if (k == 2) asm volatile("cp.async.wait_group 2;" ::: "memory");
                if (k == 3) asm volatile("cp.async.wait_group 1;" ::: "memory");
                __syncwarp();
                #pragma unroll
                for (int m = 0; m < 4; m++) {
                    uint32_t a0, a1, a2, a3;
                    ldsm4t(wa + k * 2048 + (((2 * m + sw) ^ l7) << 4), a0, a1, a2, a3);
                    mma16816(c[m], a0, a1, a2, a3, xb[2 * k], xb[2 * k + 1]);
                }
            }
            asm volatile("cp.async.wait_group 0;" ::: "memory");
            __syncwarp();
            {
                const uint32_t wt = wq_w + (64 + l7) * 128;
                #pragma unroll
                for (int m = 0; m < 4; m += 2) {
                    uint32_t a0, a1, a2, a3;
                    ldsm4t(wt + (((2 * m + (lane >> 3)) ^ l7) << 4), a0, a1, a2, a3);
                    mma1688(c[m], a0, a1, xb[8]);
                    mma1688(c[m + 1], a2, a3, xb[8]);
                }
            }
            {
                float* qr = reinterpret_cast<float*>(smem + SM_QRED) + warp * 128 + t * 16 + g;
                const float v0 = t == 0 ? c[0][0] : t == 1 ? c[1][0] : t == 2 ? c[2][0] : c[3][0];
                const float v1 = t == 0 ? c[0][1] : t == 1 ? c[1][1] : t == 2 ? c[2][1] : c[3][1];
                const float v2 = t == 0 ? c[0][2] : t == 1 ? c[1][2] : t == 2 ? c[2][2] : c[3][2];
                const float v3 = t == 0 ? c[0][3] : t == 1 ? c[1][3] : t == 2 ? c[2][3] : c[3][3];
                qr[0] = v0; qr[64] = v1; qr[8] = v2; qr[72] = v3;
            }
            bar_sync(5, 256);
            if (tid < 128) {
                const float* qr = reinterpret_cast<const float*>(smem + SM_QRED) + tid;
                float s = 0.f;
                #pragma unroll
                for (int w = 0; w < 8; w++) s += qr[w * 128];
                const float o = __shfl_xor_sync(0xffffffffu, s, 1);
                const uint32_t pk = (tid & 1) ? pack_bf16(o, s) : pack_bf16(s, o);
                const uint32_t dst = (tid >> 6) * 2 + (tid & 1);
                st_async_b32(mapa(sb + SM_QS + (rank * 64 + (tid & 62)) * 2, dst), pk, mapa(bar_xq, dst), true);
                asm volatile("fence.proxy.async.shared::cta;" ::: "memory");
                __syncwarp();
                if (lane == 0) {
                    #pragma unroll
                    for (int i = WQ_SLOT0; i < NSLOT; i++) mbar_arrive(bar_empty + 8 * i);
                }
            }
            mbar_wait(bar_xq, 0);
        }
        uint32_t qb[4][2];
        {
            const int hh = g & 1, par = (g >> 1) & 1, eta = g >> 2;
            #pragma unroll
            for (int j = 0; j < 4; j++) {
                const uint32_t a = sb + SM_QS + hh * 256 + (4 * (j ^ par) + t) * 16 + eta * 4;
                qb[j][0] = lds32(a); qb[j][1] = lds32(a + 8);
            }
        }

        const bool valid = ((t ^ g) & 1) == 0;
        const bool hi = t & 2;
        const uint32_t spr = sb + SM_SPR + warp * 2048;
        uint32_t slot = (warp >> 2) & 1, ph = 0;
        {
            const uint32_t kc0 = sb + SM_RING + ((warp & 3) * 16 + g) * 256 + (4 * (g & 1) + t) * 16;
            uint32_t sdst = spr + (t >> 1) * 64 + (g >> 1) * 16 + (g & 1) * 8;
            float mloc = -INFINITY;
            #pragma unroll 1
            for (int it = 0; it < NSTAGE; it++) {
                mbar_wait(bar_full + 8 * slot, ph);
                float ca[4] = {0.f, 0.f, 0.f, 0.f}, cb[4] = {0.f, 0.f, 0.f, 0.f};
                uint4 ka[4], kh[4];
                #pragma unroll
                for (int j = 0; j < 4; j++) {
                    const uint32_t a = slot * CHUNK + ((kc0 ^ ((j & 1) * 64)) + (j >> 1) * 128);
                    ka[j] = lds128(a); kh[j] = lds128(a + 8 * 256);
                }
                #pragma unroll
                for (int j = 0; j < 4; j++) {
                    mma16816(ca, ka[j].x, ka[j].y, ka[j].z, ka[j].w, qb[j][0], qb[j][1]);
                    mma16816(cb, kh[j].x, kh[j].y, kh[j].z, kh[j].w, qb[j][0], qb[j][1]);
                }
                __syncwarp();
                if (elect_one()) mbar_arrive(bar_empty + 8 * slot);
                slot += 2; if (slot >= NSLOT) { slot -= NSLOT; ph ^= 1; }
                const float sa = (hi ? ca[3] : ca[0]) + __shfl_xor_sync(0xffffffffu, hi ? ca[2] : ca[1], 2);
                const float sb2 = (hi ? cb[3] : cb[0]) + __shfl_xor_sync(0xffffffffu, hi ? cb[2] : cb[1], 2);
                mloc = fmaxf(mloc, fmaxf(sa, sb2));
                if (valid) asm volatile("st.shared.v2.f32 [%0], {%1, %2};" :: "r"(sdst), "f"(sa), "f"(sb2) : "memory");
                sdst += 128;
            }
            const int ko = f2ord(mloc);
            const float m0 = ord2f(__reduce_max_sync(0xffffffffu, (valid && !hi) ? ko : (int)0x80000000)) * SCALE_LOG2;
            const float m1 = ord2f(__reduce_max_sync(0xffffffffu, (valid && hi) ? ko : (int)0x80000000)) * SCALE_LOG2;
            const float mh = (lane & 4) ? m1 : m0;
            __syncwarp();
            uint4 sc[4];
            #pragma unroll
            for (int k = 0; k < 4; k++) sc[k] = lds128(spr + lane * 16 + k * 512);
            __syncwarp();
            float l = 0.f;
            #pragma unroll
            for (int k = 0; k < 4; k++) {
                const float p0 = ex2(fmaf(__uint_as_float(sc[k].x), SCALE_LOG2, -mh)), p1 = ex2(fmaf(__uint_as_float(sc[k].y), SCALE_LOG2, -mh));
                const float p2 = ex2(fmaf(__uint_as_float(sc[k].z), SCALE_LOG2, -mh)), p3 = ex2(fmaf(__uint_as_float(sc[k].w), SCALE_LOG2, -mh));
                l += (p0 + p1) + (p2 + p3);
                asm volatile("st.shared.v2.u32 [%0], {%1, %2};" :: "r"(spr + lane * 8 + k * 256), "r"(pack_bf16(p0, p1)), "r"(pack_bf16(p2, p3)) : "memory");
            }
            l += __shfl_xor_sync(0xffffffffu, l, 1);
            l += __shfl_xor_sync(0xffffffffu, l, 2);
            l += __shfl_xor_sync(0xffffffffu, l, 8);
            l += __shfl_xor_sync(0xffffffffu, l, 16);
            if ((lane & ~4) == 0) {
                reinterpret_cast<float*>(smem + SM_M)[warp * 2 + (lane >> 2)] = mh;
                reinterpret_cast<float*>(smem + SM_L)[warp * 2 + (lane >> 2)] = l;
            }
            __syncwarp();
            if (elect_one()) mbar_arrive(bar_l);
        }
        float acc[8][4];
        #pragma unroll
        for (int e = 0; e < 8; e++) { acc[e][0] = acc[e][1] = acc[e][2] = acc[e][3] = 0.f; }
        {
            const uint32_t voff = sb + SM_RING + ((warp & 3) * 16 + 2 * t) * 256 + ((g ^ (2 * t)) * 16);
            const bool bsel = (g >> 1) == t;
            uint32_t psrc = spr + ((g & 1) * 4 + t) * 8;
            #pragma unroll 1
            for (int it = 0; it < NSTAGE; it++) {
                const uint2 pw = lds64(psrc);
                psrc += 64;
                const uint32_t b0 = bsel ? pw.x : 0u, b1 = bsel ? pw.y : 0u;
                mbar_wait(bar_full + 8 * slot, ph);
                const uint32_t vb = slot * CHUNK + voff;
                const uint4 vA0 = lds128(vb), vB0 = lds128(vb + 128);
                const uint4 vA1 = lds128(vb + 8 * 256), vB1 = lds128(vb + 8 * 256 + 128);
                const uint4 vA2 = lds128(vb + 256), vB2 = lds128(vb + 256 + 128);
                const uint4 vA3 = lds128(vb + 9 * 256), vB3 = lds128(vb + 9 * 256 + 128);
                const uint32_t A0[4] = {vA0.x, vA0.y, vA0.z, vA0.w}, A1[4] = {vA1.x, vA1.y, vA1.z, vA1.w};
                const uint32_t A2[4] = {vA2.x, vA2.y, vA2.z, vA2.w}, A3[4] = {vA3.x, vA3.y, vA3.z, vA3.w};
                const uint32_t B0[4] = {vB0.x, vB0.y, vB0.z, vB0.w}, B1[4] = {vB1.x, vB1.y, vB1.z, vB1.w};
                const uint32_t B2[4] = {vB2.x, vB2.y, vB2.z, vB2.w}, B3[4] = {vB3.x, vB3.y, vB3.z, vB3.w};
                #pragma unroll
                for (int r = 0; r < 4; r++) {
                    mma16816(acc[2 * r], __byte_perm(A0[r], A1[r], 0x5410), __byte_perm(B0[r], B1[r], 0x5410),
                             __byte_perm(A2[r], A3[r], 0x5410), __byte_perm(B2[r], B3[r], 0x5410), b0, b1);
                    mma16816(acc[2 * r + 1], __byte_perm(A0[r], A1[r], 0x7632), __byte_perm(B0[r], B1[r], 0x7632),
                             __byte_perm(A2[r], A3[r], 0x7632), __byte_perm(B2[r], B3[r], 0x7632), b0, b1);
                }
                __syncwarp();
                if (elect_one()) mbar_arrive(bar_empty + 8 * slot);
                slot += 2; if (slot >= NSLOT) { slot -= NSLOT; ph ^= 1; }
            }
        }
        const int ti = tid & 255;
        {
            const bool t1 = t & 2, t0 = t & 1;
            float h16[16];
            #pragma unroll
            for (int e = 0; e < 8; e++) {
                #pragma unroll
                for (int h = 0; h < 2; h++) {
                    const float s = t1 ? acc[e][h] : acc[e][2 + h];
                    const float k = t1 ? acc[e][2 + h] : acc[e][h];
                    h16[h * 8 + e] = k + __shfl_xor_sync(0xffffffffu, s, 18);
                }
            }
            float o8[8];
            #pragma unroll
            for (int e = 0; e < 8; e++) {
                const float s = t0 ? h16[e] : h16[8 + e];
                const float k = t0 ? h16[8 + e] : h16[e];
                o8[e] = k + __shfl_xor_sync(0xffffffffu, s, 9);
            }
            const int c = g ^ (2 * t);
            float* myred = reinterpret_cast<float*>(smem + SM_SPR + warp * 2048 + 1024);
            float4* dst = reinterpret_cast<float4*>(&myred[(t & 1) * 128 + (t >> 1) * 64 + c * 8]);
            dst[t1 ? 1 : 0] = t1 ? make_float4(o8[4], o8[5], o8[6], o8[7]) : make_float4(o8[0], o8[1], o8[2], o8[3]);
            dst[t1 ? 0 : 1] = t1 ? make_float4(o8[0], o8[1], o8[2], o8[3]) : make_float4(o8[4], o8[5], o8[6], o8[7]);
            bar_sync(2, NWORK);
            const uint4 cfa = lds128(sb + SM_COEF + (ti >> 7) * 32), cfb = lds128(sb + SM_COEF + (ti >> 7) * 32 + 16);
            const float* rd = reinterpret_cast<const float*>(smem + SM_SPR + 1024) + ti;
            const float o = (fmaf(__uint_as_float(cfa.x), rd[0], __uint_as_float(cfa.y) * rd[512]) + fmaf(__uint_as_float(cfa.z), rd[1024], __uint_as_float(cfa.w) * rd[1536])) +
                            (fmaf(__uint_as_float(cfb.x), rd[2048], __uint_as_float(cfb.y) * rd[2560]) + fmaf(__uint_as_float(cfb.z), rd[3072], __uint_as_float(cfb.w) * rd[3584]));
            const float on = __shfl_xor_sync(0xffffffffu, o, 1);
            const uint32_t pk = (ti & 1) ? pack_bf16(on, o) : pack_bf16(o, on);
            const int ke = ti & ~1;
            const uint32_t pos = (ke & ~15) + ((ke & 7) >> 1) * 4 + ((ke >> 3) & 1) * 2;
            const uint32_t la = sb + SM_XO + rank * OS_PITCH + pos * 2, r0 = (ti & 1) * 2;
            st_async_b32(mapa(la, r0), pk, mapa(bar_xo, r0), true);
            st_async_b32(mapa(la, r0 + 1), pk, mapa(bar_xo, r0 + 1), true);
        }
    }

    {
        const int w9 = warp;
        uint32_t wf[16][4];
        const uint32_t wa = sb + SM_WO + ((lane & 7) + ((lane >> 4) & 1) * 8) * WO_PITCH + (w9 * 16 + ((lane >> 3) & 1) * 8) * 2;
        #pragma unroll
        for (int p = 0; p < 2; p++) {
            mbar_wait(bar_wo + 8 * p, 0);
            #pragma unroll
            for (int k = 0; k < 4; k++) ldsm4t(wa + (p * 4 + k) * 16 * WO_PITCH, wf[p * 4 + k][0], wf[p * 4 + k][1], wf[p * 4 + k][2], wf[p * 4 + k][3]);
        }
        const bool have2 = mbar_test(bar_wo + 16, 0), have3 = have2 && mbar_test(bar_wo + 24, 0);
        if (have2) {
            #pragma unroll
            for (int k = 8; k < 12; k++) ldsm4t(wa + k * 16 * WO_PITCH, wf[k][0], wf[k][1], wf[k][2], wf[k][3]);
        }
        if (have3) {
            #pragma unroll
            for (int k = 12; k < 16; k++) ldsm4t(wa + k * 16 * WO_PITCH, wf[k][0], wf[k][1], wf[k][2], wf[k][3]);
        }
        mbar_wait(bar_xo, 0);
        float ya[4] = {0.f, 0.f, 0.f, 0.f}, yb[4] = {0.f, 0.f, 0.f, 0.f}, yc[4] = {0.f, 0.f, 0.f, 0.f}, yd[4] = {0.f, 0.f, 0.f, 0.f};
        const uint32_t oa = sb + SM_XO + (g & 3) * OS_PITCH + t * 8;
        uint2 bf[16];
        #pragma unroll
        for (int k = 0; k < 16; k++) bf[k] = lds64(oa + k * 32);
        #pragma unroll
        for (int k = 0; k < 8; k += 4) {
            mma16816(ya, wf[k][0], wf[k][1], wf[k][2], wf[k][3], bf[k].x, bf[k].y);
            mma16816(yb, wf[k + 1][0], wf[k + 1][1], wf[k + 1][2], wf[k + 1][3], bf[k + 1].x, bf[k + 1].y);
            mma16816(yc, wf[k + 2][0], wf[k + 2][1], wf[k + 2][2], wf[k + 2][3], bf[k + 2].x, bf[k + 2].y);
            mma16816(yd, wf[k + 3][0], wf[k + 3][1], wf[k + 3][2], wf[k + 3][3], bf[k + 3].x, bf[k + 3].y);
        }
        if (!have2) {
            mbar_wait(bar_wo + 16, 0);
            #pragma unroll
            for (int k = 8; k < 12; k++) ldsm4t(wa + k * 16 * WO_PITCH, wf[k][0], wf[k][1], wf[k][2], wf[k][3]);
        }
        mma16816(ya, wf[8][0], wf[8][1], wf[8][2], wf[8][3], bf[8].x, bf[8].y);
        mma16816(yb, wf[9][0], wf[9][1], wf[9][2], wf[9][3], bf[9].x, bf[9].y);
        mma16816(yc, wf[10][0], wf[10][1], wf[10][2], wf[10][3], bf[10].x, bf[10].y);
        mma16816(yd, wf[11][0], wf[11][1], wf[11][2], wf[11][3], bf[11].x, bf[11].y);
        if (!have3) {
            mbar_wait(bar_wo + 24, 0);
            #pragma unroll
            for (int k = 12; k < 16; k++) ldsm4t(wa + k * 16 * WO_PITCH, wf[k][0], wf[k][1], wf[k][2], wf[k][3]);
        }
        mma16816(ya, wf[12][0], wf[12][1], wf[12][2], wf[12][3], bf[12].x, bf[12].y);
        mma16816(yb, wf[13][0], wf[13][1], wf[13][2], wf[13][3], bf[13].x, bf[13].y);
        mma16816(yc, wf[14][0], wf[14][1], wf[14][2], wf[14][3], bf[14].x, bf[14].y);
        mma16816(yd, wf[15][0], wf[15][1], wf[15][2], wf[15][3], bf[15].x, bf[15].y);
        {
            const float y_lo = ((ya[0] + yb[0]) + (yc[0] + yd[0])) + ((ya[1] + yb[1]) + (yc[1] + yd[1]));
            const float y_hi = ((ya[2] + yb[2]) + (yc[2] + yd[2])) + ((ya[3] + yb[3]) + (yc[3] + yd[3]));
            const int n = (t & 1) * D_MODEL + rank * 144 + w9 * 16 + (t >> 1) * 8 + g;
            const float y = (t & 2) ? y_hi : y_lo;
            float s0, c0;
            asm volatile("atom.relaxed.gpu.global.add.v2.f32 {%0, %1}, [%2], {%3, %4};" : "=f"(s0), "=f"(c0) : "l"(&g_acc[n]), "f"(y), "f"(1.0f) : "memory");
            if (c0 == 15.0f) out[n] = __float2bfloat16(s0 + y);
        }
    }
}

typedef CUresult (*EncodeFn)(CUtensorMap*, CUtensorMapDataType, cuuint32_t, void*, const cuuint64_t*, const cuuint64_t*,
                             const cuuint32_t*, const cuuint32_t*, CUtensorMapInterleave, CUtensorMapSwizzle,
                             CUtensorMapL2promotion, CUtensorMapFloatOOBfill);
}

extern "C" void kernel_launch(void* const* d_in, const int* in_sizes, int n_in, void* d_out, int out_size) {
    (void)in_sizes; (void)n_in; (void)out_size;
    static CUtensorMap wo_map;
    static const void* mapped = nullptr;
    if (mapped != d_in[4]) {
        void* fn = nullptr; cudaDriverEntryPointQueryResult qr;
        cudaGetDriverEntryPoint("cuTensorMapEncodeTiled", &fn, cudaEnableDefault, &qr);
        cuuint64_t dims[2] = {(cuuint64_t)D_MODEL, (cuuint64_t)NQ};
        cuuint64_t strides[1] = {(cuuint64_t)D_MODEL * 2};
        cuuint32_t box[2] = {152, 64}; cuuint32_t es[2] = {1, 1};
        ((EncodeFn)fn)(&wo_map, CU_TENSOR_MAP_DATA_TYPE_BFLOAT16, 2, d_in[4], dims, strides, box, es,
                       CU_TENSOR_MAP_INTERLEAVE_NONE, CU_TENSOR_MAP_SWIZZLE_NONE, CU_TENSOR_MAP_L2_PROMOTION_L2_128B,
                       CU_TENSOR_MAP_FLOAT_OOB_FILL_NONE);
        cudaFuncSetAttribute(fused_decode_kernel, cudaFuncAttributeMaxDynamicSharedMemorySize, SM_TOTAL);
        mapped = d_in[4];
    }
    fused_decode_kernel<<<NCTA, NTHREADS, SM_TOTAL, cudaStreamPerThread>>>(
        (const __nv_bfloat16*)d_in[0], (const __nv_bfloat16*)d_in[1], (const __nv_bfloat16*)d_in[2],
        (const __nv_bfloat16*)d_in[3], (__nv_bfloat16*)d_out, wo_map);
}
```
